```python
import torch

def _softmax(x, axis=-1):
    return torch.softmax(x, dim=axis)
def _gelu(x):
    return torch.nn.functional.gelu(x, approximate="tanh")
def _silu(x):
    return torch.nn.functional.silu(x)
def _sigmoid(x):
    return torch.sigmoid(x)
def _layernorm(x, axis=-1, eps=1e-5):
    m = x.mean(dim=axis, keepdim=True)
    v = x.var(dim=axis, keepdim=True, unbiased=False)
    return (x - m) / torch.sqrt(v + eps)
def _scatter_add(tgt, idx, src, axis=0):
    return tgt.clone().index_add_(axis, idx, src)
def _segment_sum(src, seg, n):
    out = torch.zeros((n,) + src.shape[1:], dtype=src.dtype)
    return out.index_add_(0, seg, src)
def _pad(x, pw):
    flat = tuple(v for pair in reversed(pw) for v in pair)
    return torch.nn.functional.pad(x, flat)

kernel_name = 'interleave_layers__sliding_local_dilated__dense_activation_relu__prompt'

def setup_inputs():

    _w = (lambda a: (lambda t: t.to(torch.bfloat16) if t.is_floating_point() else t)(torch.as_tensor(a)))
    def _A_setup():
        B, S, D = 1, 2048, 640
        return {
            "x": _w((lambda *s: torch.randn(*s, dtype=torch.bfloat16) * 0.05)(B, S, D)),
            "wqkv": _w((lambda *s: torch.randn(*s, dtype=torch.bfloat16) * 0.05)(D, 3 * D)),
            "wo": _w((lambda *s: torch.randn(*s, dtype=torch.bfloat16) * 0.05)(D, D)),
        }
    _A_in = _A_setup()

    def _B_setup():
        B, S, D, Dff = 1, 2048, 640, 1728
        return {
            "x": _w((lambda *s: torch.randn(*s, dtype=torch.bfloat16) * 0.05)(B, S, D)),
            "w1": _w((lambda *s: torch.randn(*s, dtype=torch.bfloat16) * 0.05)(D, Dff)),
            "w2": _w((lambda *s: torch.randn(*s, dtype=torch.bfloat16) * 0.05)(Dff, D)),
        }
    _B_in = _B_setup()

    return {
        "A_x": _A_in["x"],
        "A_wqkv": _A_in["wqkv"],
        "A_wo": _A_in["wo"],
        "B_x": _B_in["x"],
        "B_w1": _B_in["w1"],
        "B_w2": _B_in["w2"],
    }

def reference(A_x, A_wqkv, A_wo, B_x, B_w1, B_w2):
    def _A_ref(x, wqkv, wo):
        B, S, D = x.shape
        H = 32; Dh = D // H
        W, dil = 8, 2
        qkv = (lambda x, *d: x.permute(*d))((x @ wqkv).reshape(B, S, 3, H, Dh), 2, 0, 3, 1, 4)
        q, k, v = qkv[0], qkv[1], qkv[2]
        scale = Dh ** -0.5
        pos = torch.arange(S)
        off = torch.arange(W) * dil
        idx = pos[:, None] - off[None, :]
        mask = idx >= 0
        idx_c = torch.where(mask, idx, 0).reshape(-1)
        kg = k[:, :, idx_c, :].reshape(B, H, S, W, Dh)
        vg = v[:, :, idx_c, :].reshape(B, H, S, W, Dh)
        logits = torch.einsum("bhsd,bhswd->bhsw", q, kg) * scale
        logits = torch.where(mask[None, None, :, :], logits, -1e9)
        attn = _softmax(logits, axis=-1)
        o = torch.einsum("bhsw,bhswd->bhsd", attn, vg)
        return (lambda x, *d: x.permute(*d))(o, 0, 2, 1, 3).reshape(B, S, D) @ wo

    def _B_ref(x, w1, w2):
        h = torch.einsum("bsd,df->bsf", x, w1)
        zero = torch.zeros_like(h)
        h = torch.maximum(h, zero)
        return torch.einsum("bsf,fd->bsd", h, w2)

    x = A_x
    x = x + _A_ref(_layernorm(x, axis=-1), A_wqkv, A_wo)
    x = x + _B_ref(_layernorm(x, axis=-1), B_w1, B_w2)
    x = x + _A_ref(_layernorm(x, axis=-1), A_wqkv, A_wo)
    x = x + _B_ref(_layernorm(x, axis=-1), B_w1, B_w2)
    return x
```

```cpp
#include <cuda_runtime.h>
#include <cuda_bf16.h>
#include <cuda.h>
#include <stdint.h>

#define DBG_STAGE 4
#define TLSEL 0
#define FLAG_POS 5
#define CS_GATE0 2
#define CS_GATE1 13
#define INFLIGHT 2
#define LAG_MASK 15
#define NB0_LN 1
#define NB0_WO 3
#define POLL_NS 64
#define EARLY_FETCH 0
#define PAUSE_WO 0
#define PARTNER_FIRST 1
#define WO_B1 2
#define WO_B2 5
#define REG_HELP 56
#define REG_CONS 224
#define CS_BATCH 5
#define CS_GB 8
#define CLEAR_H 3
#define XFIRST 4
#define XGATE 0
#define XCLEAR 0
#define CS_LOAD0 -1
#define CS_LOAD1 3
#define SWAP 1
#define PF_STEPS 0
#define NOMC 2
#define CS_PRE -1
#define CS_SLEEP 300
#define ORDER 0x694
#define CLR_NS 40
#define MOVM_SHADOW 0
#define BPF 0
#define BPF_A 3
#define BPF_B 8
#define LAG_STEPS 0

namespace {

constexpr int DM = 640, DQKV = 1920, DFF = 1728;
constexpr int NITEMS_L = 30, NITEMS = 60;
constexpr int IT_WO = 9, IT_W1 = 13, IT_W2 = 21;
constexpr float LN_EPS = 1e-5f;
constexpr int SPIN_BUDGET = 1 << 20;

constexpr int RING_BYTES = 198 * 1024;
constexpr int OFF_XQM = RING_BYTES;
constexpr int OFF_XW1 = OFF_XQM + 3072;
constexpr int OFF_XQR = OFF_XW1 + 3584;
constexpr int XTRA_BYTES = 7424;
constexpr int OFF_PARK = OFF_XQM + XTRA_BYTES;
constexpr int OFF_BAR = OFF_PARK + 8 * 2560;
constexpr int BAR_FULL = OFF_BAR, BAR_EMPTY = OFF_BAR + NITEMS * 8, BAR_CS = OFF_BAR + 2 * NITEMS * 8;
constexpr int NORD = 12;
constexpr int BAR_ORD = BAR_CS + 16;
constexpr int OFF_RK = BAR_ORD + 2 * NORD * 8;
constexpr int SMEM_BYTES = OFF_RK + 256;
static_assert(SMEM_BYTES <= 232448, "smem");

constexpr int STAGE_ITEM = 4, STAGE_BAR = NITEMS - 1;
struct ItemTab { int off[NITEMS]; int dep[NITEMS]; int rel[NITEMS]; };
constexpr int item_size(int k) {
    constexpr int kb[NITEMS_L] = {38, 38, 38, 38, 38, 28, 28, 28, 30, 30, 30, 30, 30, 35, 35, 35, 35, 35, 35, 30, 40, 30, 40, 30, 30, 30, 40, 24, 24, 32};
    return kb[k] * 1024;
}
constexpr ItemTab make_tab() {
    constexpr int kb[NITEMS] = {0, 38, 160, 122, 84, 56, 28, 0, 160, 130, 100, 70, 40, 0, 160, 125, 70, 35, 0, 168, 128, 98, 58, 0, 168, 138, 98, 34, 58, 0,
                                160, 82, 120, 44, 0, 170, 82, 110, 138, 38, 0, 168, 80, 110, 38, 0, 163, 73, 128, 43, 0, 163, 88, 128, 58, 0, 158, 30, 88, 112};
    ItemTab t{};
    int seen = -1;
    for (int i = 0; i < NITEMS; i++) {
        const int s = item_size(i % NITEMS_L), o = kb[i] * 1024;
        t.off[i] = o;
        int d = -1;
        for (int j = i - 1; j >= 0; j--) {
            const int sj = item_size(j % NITEMS_L);
            if (t.off[j] < o + s && o < t.off[j] + sj) { d = j; break; }
        }
        if (PAUSE_WO && i % NITEMS_L == IT_W1 + PAUSE_WO && d < i - PAUSE_WO - 2) d = i - PAUSE_WO - 2;
        t.dep[i] = d > seen ? d : -1;
        if (d > seen) seen = d;
        t.rel[i] = 0;
    }
    for (int i = 0; i < NITEMS; i++) if (t.dep[i] >= 0) t.rel[t.dep[i]] = 1;
    t.rel[CS_LOAD1] = 1;
    t.dep[STAGE_ITEM] = STAGE_BAR;
    return t;
}
constexpr int STAGE_OFF = 76 * 1024, STAGE_BYTES = 128 * 336;
constexpr bool tab_ok() {
    const ItemTab t = make_tab();
    for (int i = 0; i < STAGE_ITEM; i++)
        if (t.dep[i] >= 0 || (t.off[i] < STAGE_OFF + STAGE_BYTES && STAGE_OFF < t.off[i] + item_size(i))) return false;
    if (t.rel[STAGE_BAR]) return false;
    for (int i = 0; i < NITEMS; i++)
        if (t.off[i] + item_size(i % NITEMS_L) > RING_BYTES || (i != STAGE_ITEM && t.dep[i] >= 0 && i - t.dep[i] < 4)) return false;
    return true;
}
static_assert(tab_ok(), "ring schedule");
struct Params {
    char* scr;
    const __nv_bfloat16 *xin, *wqkv, *w1, *wo, *w2;
    __nv_bfloat16* out;
    int minus1, pad;
    uint8_t role[64];
    uint32_t item[NITEMS];
};

constexpr int SLAB = 20480;
constexpr int EX_X = 0, EX_O = 128;
constexpr int HSLAB = 57344;
constexpr uint32_t G_H = 256 * SLAB;
constexpr uint32_t G_XST = G_H + 128 * HSLAB;
constexpr uint32_t G_HALO = G_XST + 16 * 8 * 8 * 128;
constexpr uint32_t G_CS = G_HALO + 2 * 128 * 2 * 3072;
constexpr uint32_t G_EPOCH = G_CS + 8 * 2 * 3 * 5120;
constexpr uint32_t G_BYTES = G_EPOCH + 128 * 128;
__device__ uint4 g_scratch[G_BYTES / 16];
#define TL(slot) do {} while (0)
#define TLB(slot) do {} while (0)
#define TLH(slot) do {} while (0)
#define TLDUMP(n) do {} while (0)
#define TLINIT
constexpr int SMEM_LAUNCH = SMEM_BYTES;

#define PROBE 0
#define PR(on, i) do {} while (0)
#define PRB(on, i) do {} while (0)
#define PRDUMP(on) do {} while (0)
#define UNLIKELY(x) __builtin_expect(!!(x), 0)
__device__ __forceinline__ uint32_t smem_u32(const void* p) { return (uint32_t)__cvta_generic_to_shared(p); }
__device__ __forceinline__ void mbar_init(uint32_t b, int c) { asm volatile("mbarrier.init.shared::cta.b64 [%0], %1;" :: "r"(b), "r"(c) : "memory"); }
__device__ __forceinline__ void mbar_expect(uint32_t b, int bytes) { asm volatile("mbarrier.arrive.expect_tx.shared::cta.b64 _, [%0], %1;" :: "r"(b), "r"(bytes) : "memory"); }
__device__ __forceinline__ void mbar_arrive(uint32_t b) { asm volatile("mbarrier.arrive.shared::cta.b64 _, [%0];" :: "r"(b) : "memory"); }
__device__ __forceinline__ void mbar_arrive_cluster(uint32_t b) { asm volatile("mbarrier.arrive.shared::cluster.b64 _, [%0];" :: "r"(b) : "memory"); }
__device__ __forceinline__ void mbar_wait0(uint32_t b, int& budget) {
    uint32_t ok;
#pragma unroll 1
    do {
        asm volatile("{.reg .pred p; mbarrier.try_wait.parity.shared::cta.b64 p, [%1], 0; selp.u32 %0, 1, 0, p;}" : "=r"(ok) : "r"(b) : "memory");
    } while (UNLIKELY(!ok) && --budget >= 0);
}
__device__ __forceinline__ void ldv(uint32_t (&v)[4], const void* p) {
    asm volatile("{.reg .b128 t; ld.relaxed.gpu.global.b128 t, [%4]; mov.b128 {%0,%1,%2,%3}, t;}"
                 : "=r"(v[0]), "=r"(v[1]), "=r"(v[2]), "=r"(v[3]) : "l"(p) : "memory");
}
__device__ __forceinline__ void stv(void* p, uint32_t a, uint32_t b, uint32_t c, uint32_t d) {
    asm volatile("{.reg .b128 t; mov.b128 t, {%0,%1,%2,%3}; st.relaxed.gpu.global.b128 [%4], t;}"
                 :: "r"(a), "r"(b), "r"(c), "r"(d), "l"(p) : "memory");
}
__device__ __forceinline__ uint32_t tagged(uint32_t w, uint32_t tag) { return (w & ~1u) | tag; }
__device__ __forceinline__ uint32_t pack2(float lo, float hi) {
    uint32_t r; asm("cvt.rn.bf16x2.f32 %0, %1, %2;" : "=r"(r) : "f"(hi), "f"(lo)); return r;
}
__device__ __forceinline__ uint32_t pack2_relu(float lo, float hi) {
    uint32_t r; asm("cvt.rn.relu.bf16x2.f32 %0, %1, %2;" : "=r"(r) : "f"(hi), "f"(lo)); return r;
}
__device__ __forceinline__ float bf_lo(uint32_t w) { return __uint_as_float(w << 16); }
__device__ __forceinline__ float bf_hi(uint32_t w) { return __uint_as_float(w & 0xffff0000u); }
__device__ __forceinline__ uint32_t movm(uint32_t a) {
    uint32_t r; asm volatile("movmatrix.sync.aligned.m8n8.trans.b16 %0, %1;" : "=r"(r) : "r"(a)); return r;
}
__device__ __forceinline__ float ex2(float x) { float r; asm("ex2.approx.ftz.f32 %0, %1;" : "=f"(r) : "f"(x)); return r; }
__device__ __forceinline__ float rcp(float x) { float r; asm("rcp.approx.ftz.f32 %0, %1;" : "=f"(r) : "f"(x)); return r; }
__device__ __forceinline__ void mma_k8_init(float (&d)[4], uint32_t a0, uint32_t a1, uint32_t b0) {
    asm volatile("mma.sync.aligned.m16n8k8.row.col.f32.bf16.bf16.f32 {%0,%1,%2,%3}, {%4,%5}, {%6}, {%7,%7,%7,%7};"
                 : "=f"(d[0]), "=f"(d[1]), "=f"(d[2]), "=f"(d[3]) : "r"(a0), "r"(a1), "r"(b0), "f"(0.f));
}
__device__ __forceinline__ void mma_k16_acc(float (&d)[4], uint32_t a0, uint32_t a1, uint32_t a2, uint32_t a3, uint32_t b0, uint32_t b1) {
    asm volatile("mma.sync.aligned.m16n8k16.row.col.f32.bf16.bf16.f32 {%0,%1,%2,%3}, {%4,%5,%6,%7}, {%8,%9}, {%0,%1,%2,%3};"
                 : "+f"(d[0]), "+f"(d[1]), "+f"(d[2]), "+f"(d[3]) : "r"(a0), "r"(a1), "r"(a2), "r"(a3), "r"(b0), "r"(b1));
}
__device__ __forceinline__ void wg_fence() { asm volatile("wgmma.fence.sync.aligned;" ::: "memory"); }
__device__ __forceinline__ void wg_commit() { asm volatile("wgmma.commit_group.sync.aligned;" ::: "memory"); }
template <int N> __device__ __forceinline__ void wg_wait() { asm volatile("wgmma.wait_group.sync.aligned %0;" :: "n"(N) : "memory"); }
template <int N> __device__ __forceinline__ void reg_fence(float (&d)[N]) {
#pragma unroll
    for (int i = 0; i < N; i++) asm volatile("" : "+f"(d[i]) :: "memory");
}
__device__ __forceinline__ uint64_t mkdesc(uint32_t a16, uint32_t off, uint32_t lbo, uint32_t sbo, int sw) {
    const uint32_t lo = a16 + ((off >> 4) + ((lbo >> 4) << 16));
    const uint32_t hi = (sbo >> 4) | ((uint32_t)sw << 30);
    return ((uint64_t)hi << 32) | lo;
}
__device__ __forceinline__ bool elect_one() {
    uint32_t p;
    asm volatile("{.reg .pred q; elect.sync _|q, 0xffffffff; selp.u32 %0, 1, 0, q;}" : "=r"(p));
    return p;
}
__device__ __forceinline__ int launder(int v) { asm volatile("" : "+r"(v)); return v; }
__device__ __forceinline__ void tma2d_mc(uint32_t dst, const CUtensorMap* tm, int c0, int c1, uint32_t bar) {
    asm volatile("cp.async.bulk.tensor.2d.shared::cluster.global.mbarrier::complete_tx::bytes.multicast::cluster [%0], [%1, {%3, %4}], [%2], %5;"
                 :: "r"(dst), "l"(tm), "r"(bar), "r"(c0), "r"(c1), "h"((uint16_t)3) : "memory");
}
__device__ __forceinline__ void l2_prefetch(const void* p, uint32_t bytes) {
    asm volatile("cp.async.bulk.prefetch.L2.global [%0], %1;" :: "l"(p), "r"(bytes) : "memory");
}
__device__ __forceinline__ void tma2d(uint32_t dst, const CUtensorMap* tm, int c0, int c1, uint32_t bar) {
    asm volatile("cp.async.bulk.tensor.2d.shared::cluster.global.mbarrier::complete_tx::bytes [%0], [%1, {%3, %4}], [%2];"
                 :: "r"(dst), "l"(tm), "r"(bar), "r"(c0), "r"(c1) : "memory");
}
__device__ __forceinline__ void tma3d(uint32_t dst, const CUtensorMap* tm, int c0, int c1, int c2, uint32_t bar) {
    asm volatile("cp.async.bulk.tensor.3d.shared::cluster.global.mbarrier::complete_tx::bytes [%0], [%1, {%3, %4, %5}], [%2];"
                 :: "r"(dst), "l"(tm), "r"(bar), "r"(c0), "r"(c1), "r"(c2) : "memory");
}
__device__ __forceinline__ void tma3d_mc(uint32_t dst, const CUtensorMap* tm, int c0, int c1, int c2, uint32_t bar) {
    asm volatile("cp.async.bulk.tensor.3d.shared::cluster.global.mbarrier::complete_tx::bytes.multicast::cluster [%0], [%1, {%3, %4, %5}], [%2], %6;"
                 :: "r"(dst), "l"(tm), "r"(bar), "r"(c0), "r"(c1), "r"(c2), "h"((uint16_t)3) : "memory");
}

__device__ __forceinline__ void wgmma_n192_acc(float (&d)[96], const uint32_t (&a)[4], uint64_t db) {
    asm volatile("{.reg .pred p; setp.eq.b32 p, 0, 0;\n"
        "wgmma.mma_async.sync.aligned.m64n192k16.f32.bf16.bf16 {"
        "%0, %1, %2, %3, %4, %5, %6, %7, %8, %9, %10, %11, %12, %13, %14, %15, %16, %17, %18, %19, %20, %21, %22, %23, "
        "%24, %25, %26, %27, %28, %29, %30, %31, %32, %33, %34, %35, %36, %37, %38, %39, %40, %41, %42, %43, %44, %45, %46, %47, "
        "%48, %49, %50, %51, %52, %53, %54, %55, %56, %57, %58, %59, %60, %61, %62, %63, %64, %65, %66, %67, %68, %69, %70, %71, "
        "%72, %73, %74, %75, %76, %77, %78, %79, %80, %81, %82, %83, %84, %85, %86, %87, %88, %89, %90, %91, %92, %93, %94, %95"
        "}, {%96, %97, %98, %99}, %100, p, 1, 1, 1;}\n"
        : "+f"(d[0]), "+f"(d[1]), "+f"(d[2]), "+f"(d[3]), "+f"(d[4]), "+f"(d[5]), "+f"(d[6]), "+f"(d[7]), "+f"(d[8]), "+f"(d[9]), "+f"(d[10]), "+f"(d[11]),
          "+f"(d[12]), "+f"(d[13]), "+f"(d[14]), "+f"(d[15]), "+f"(d[16]), "+f"(d[17]), "+f"(d[18]), "+f"(d[19]), "+f"(d[20]), "+f"(d[21]), "+f"(d[22]), "+f"(d[23]),
          "+f"(d[24]), "+f"(d[25]), "+f"(d[26]), "+f"(d[27]), "+f"(d[28]), "+f"(d[29]), "+f"(d[30]), "+f"(d[31]), "+f"(d[32]), "+f"(d[33]), "+f"(d[34]), "+f"(d[35]),
          "+f"(d[36]), "+f"(d[37]), "+f"(d[38]), "+f"(d[39]), "+f"(d[40]), "+f"(d[41]), "+f"(d[42]), "+f"(d[43]), "+f"(d[44]), "+f"(d[45]), "+f"(d[46]), "+f"(d[47]),
          "+f"(d[48]), "+f"(d[49]), "+f"(d[50]), "+f"(d[51]), "+f"(d[52]), "+f"(d[53]), "+f"(d[54]), "+f"(d[55]), "+f"(d[56]), "+f"(d[57]), "+f"(d[58]), "+f"(d[59]),
          "+f"(d[60]), "+f"(d[61]), "+f"(d[62]), "+f"(d[63]), "+f"(d[64]), "+f"(d[65]), "+f"(d[66]), "+f"(d[67]), "+f"(d[68]), "+f"(d[69]), "+f"(d[70]), "+f"(d[71]),
          "+f"(d[72]), "+f"(d[73]), "+f"(d[74]), "+f"(d[75]), "+f"(d[76]), "+f"(d[77]), "+f"(d[78]), "+f"(d[79]), "+f"(d[80]), "+f"(d[81]), "+f"(d[82]), "+f"(d[83]),
          "+f"(d[84]), "+f"(d[85]), "+f"(d[86]), "+f"(d[87]), "+f"(d[88]), "+f"(d[89]), "+f"(d[90]), "+f"(d[91]), "+f"(d[92]), "+f"(d[93]), "+f"(d[94]), "+f"(d[95])
        : "r"(a[0]), "r"(a[1]), "r"(a[2]), "r"(a[3]), "l"(db));
}
__device__ __forceinline__ void wgmma_n192_init(float (&d)[96], const uint32_t (&a)[4], uint64_t db) {
    asm volatile("{.reg .pred p; setp.ne.b32 p, 0, 0;\n"
        "wgmma.mma_async.sync.aligned.m64n192k16.f32.bf16.bf16 {"
        "%0, %1, %2, %3, %4, %5, %6, %7, %8, %9, %10, %11, %12, %13, %14, %15, %16, %17, %18, %19, %20, %21, %22, %23, "
        "%24, %25, %26, %27, %28, %29, %30, %31, %32, %33, %34, %35, %36, %37, %38, %39, %40, %41, %42, %43, %44, %45, %46, %47, "
        "%48, %49, %50, %51, %52, %53, %54, %55, %56, %57, %58, %59, %60, %61, %62, %63, %64, %65, %66, %67, %68, %69, %70, %71, "
        "%72, %73, %74, %75, %76, %77, %78, %79, %80, %81, %82, %83, %84, %85, %86, %87, %88, %89, %90, %91, %92, %93, %94, %95"
        "}, {%96, %97, %98, %99}, %100, p, 1, 1, 1;}\n"
        : "=f"(d[0]), "=f"(d[1]), "=f"(d[2]), "=f"(d[3]), "=f"(d[4]), "=f"(d[5]), "=f"(d[6]), "=f"(d[7]), "=f"(d[8]), "=f"(d[9]), "=f"(d[10]), "=f"(d[11]),
          "=f"(d[12]), "=f"(d[13]), "=f"(d[14]), "=f"(d[15]), "=f"(d[16]), "=f"(d[17]), "=f"(d[18]), "=f"(d[19]), "=f"(d[20]), "=f"(d[21]), "=f"(d[22]), "=f"(d[23]),
          "=f"(d[24]), "=f"(d[25]), "=f"(d[26]), "=f"(d[27]), "=f"(d[28]), "=f"(d[29]), "=f"(d[30]), "=f"(d[31]), "=f"(d[32]), "=f"(d[33]), "=f"(d[34]), "=f"(d[35]),
          "=f"(d[36]), "=f"(d[37]), "=f"(d[38]), "=f"(d[39]), "=f"(d[40]), "=f"(d[41]), "=f"(d[42]), "=f"(d[43]), "=f"(d[44]), "=f"(d[45]), "=f"(d[46]), "=f"(d[47]),
          "=f"(d[48]), "=f"(d[49]), "=f"(d[50]), "=f"(d[51]), "=f"(d[52]), "=f"(d[53]), "=f"(d[54]), "=f"(d[55]), "=f"(d[56]), "=f"(d[57]), "=f"(d[58]), "=f"(d[59]),
          "=f"(d[60]), "=f"(d[61]), "=f"(d[62]), "=f"(d[63]), "=f"(d[64]), "=f"(d[65]), "=f"(d[66]), "=f"(d[67]), "=f"(d[68]), "=f"(d[69]), "=f"(d[70]), "=f"(d[71]),
          "=f"(d[72]), "=f"(d[73]), "=f"(d[74]), "=f"(d[75]), "=f"(d[76]), "=f"(d[77]), "=f"(d[78]), "=f"(d[79]), "=f"(d[80]), "=f"(d[81]), "=f"(d[82]), "=f"(d[83]),
          "=f"(d[84]), "=f"(d[85]), "=f"(d[86]), "=f"(d[87]), "=f"(d[88]), "=f"(d[89]), "=f"(d[90]), "=f"(d[91]), "=f"(d[92]), "=f"(d[93]), "=f"(d[94]), "=f"(d[95])
        : "r"(a[0]), "r"(a[1]), "r"(a[2]), "r"(a[3]), "l"(db));
}
__device__ __forceinline__ void wgmma_n48_acc(float (&d)[24], const uint32_t (&a)[4], uint64_t db) {
    asm volatile("{.reg .pred p; setp.eq.b32 p, 0, 0;\n"
        "wgmma.mma_async.sync.aligned.m64n48k16.f32.bf16.bf16 {"
        "%0, %1, %2, %3, %4, %5, %6, %7, %8, %9, %10, %11, %12, %13, %14, %15, %16, %17, %18, %19, %20, %21, %22, %23"
        "}, {%24, %25, %26, %27}, %28, p, 1, 1, 1;}\n"
        : "+f"(d[0]), "+f"(d[1]), "+f"(d[2]), "+f"(d[3]), "+f"(d[4]), "+f"(d[5]), "+f"(d[6]), "+f"(d[7]), "+f"(d[8]), "+f"(d[9]), "+f"(d[10]), "+f"(d[11]),
          "+f"(d[12]), "+f"(d[13]), "+f"(d[14]), "+f"(d[15]), "+f"(d[16]), "+f"(d[17]), "+f"(d[18]), "+f"(d[19]), "+f"(d[20]), "+f"(d[21]), "+f"(d[22]), "+f"(d[23])
        : "r"(a[0]), "r"(a[1]), "r"(a[2]), "r"(a[3]), "l"(db));
}
__device__ __forceinline__ void wgmma_n48_init(float (&d)[24], const uint32_t (&a)[4], uint64_t db) {
    asm volatile("{.reg .pred p; setp.ne.b32 p, 0, 0;\n"
        "wgmma.mma_async.sync.aligned.m64n48k16.f32.bf16.bf16 {"
        "%0, %1, %2, %3, %4, %5, %6, %7, %8, %9, %10, %11, %12, %13, %14, %15, %16, %17, %18, %19, %20, %21, %22, %23"
        "}, {%24, %25, %26, %27}, %28, p, 1, 1, 1;}\n"
        : "=f"(d[0]), "=f"(d[1]), "=f"(d[2]), "=f"(d[3]), "=f"(d[4]), "=f"(d[5]), "=f"(d[6]), "=f"(d[7]), "=f"(d[8]), "=f"(d[9]), "=f"(d[10]), "=f"(d[11]),
          "=f"(d[12]), "=f"(d[13]), "=f"(d[14]), "=f"(d[15]), "=f"(d[16]), "=f"(d[17]), "=f"(d[18]), "=f"(d[19]), "=f"(d[20]), "=f"(d[21]), "=f"(d[22]), "=f"(d[23])
        : "r"(a[0]), "r"(a[1]), "r"(a[2]), "r"(a[3]), "l"(db));
}
__device__ __forceinline__ void wgmma_n224_acc(float (&d)[112], const uint32_t (&a)[4], uint64_t db) {
    asm volatile("{.reg .pred p; setp.eq.b32 p, 0, 0;\n"
        "wgmma.mma_async.sync.aligned.m64n224k16.f32.bf16.bf16 {"
        "%0, %1, %2, %3, %4, %5, %6, %7, %8, %9, %10, %11, %12, %13, %14, %15, %16, %17, %18, %19, %20, %21, %22, %23, "
        "%24, %25, %26, %27, %28, %29, %30, %31, %32, %33, %34, %35, %36, %37, %38, %39, %40, %41, %42, %43, %44, %45, %46, %47, "
        "%48, %49, %50, %51, %52, %53, %54, %55, %56, %57, %58, %59, %60, %61, %62, %63, %64, %65, %66, %67, %68, %69, %70, %71, "
        "%72, %73, %74, %75, %76, %77, %78, %79, %80, %81, %82, %83, %84, %85, %86, %87, %88, %89, %90, %91, %92, %93, %94, %95, "
        "%96, %97, %98, %99, %100, %101, %102, %103, %104, %105, %106, %107, %108, %109, %110, %111"
        "}, {%112, %113, %114, %115}, %116, p, 1, 1, 1;}\n"
        : "+f"(d[0]), "+f"(d[1]), "+f"(d[2]), "+f"(d[3]), "+f"(d[4]), "+f"(d[5]), "+f"(d[6]), "+f"(d[7]), "+f"(d[8]), "+f"(d[9]), "+f"(d[10]), "+f"(d[11]),
          "+f"(d[12]), "+f"(d[13]), "+f"(d[14]), "+f"(d[15]), "+f"(d[16]), "+f"(d[17]), "+f"(d[18]), "+f"(d[19]), "+f"(d[20]), "+f"(d[21]), "+f"(d[22]), "+f"(d[23]),
          "+f"(d[24]), "+f"(d[25]), "+f"(d[26]), "+f"(d[27]), "+f"(d[28]), "+f"(d[29]), "+f"(d[30]), "+f"(d[31]), "+f"(d[32]), "+f"(d[33]), "+f"(d[34]), "+f"(d[35]),
          "+f"(d[36]), "+f"(d[37]), "+f"(d[38]), "+f"(d[39]), "+f"(d[40]), "+f"(d[41]), "+f"(d[42]), "+f"(d[43]), "+f"(d[44]), "+f"(d[45]), "+f"(d[46]), "+f"(d[47]),
          "+f"(d[48]), "+f"(d[49]), "+f"(d[50]), "+f"(d[51]), "+f"(d[52]), "+f"(d[53]), "+f"(d[54]), "+f"(d[55]), "+f"(d[56]), "+f"(d[57]), "+f"(d[58]), "+f"(d[59]),
          "+f"(d[60]), "+f"(d[61]), "+f"(d[62]), "+f"(d[63]), "+f"(d[64]), "+f"(d[65]), "+f"(d[66]), "+f"(d[67]), "+f"(d[68]), "+f"(d[69]), "+f"(d[70]), "+f"(d[71]),
          "+f"(d[72]), "+f"(d[73]), "+f"(d[74]), "+f"(d[75]), "+f"(d[76]), "+f"(d[77]), "+f"(d[78]), "+f"(d[79]), "+f"(d[80]), "+f"(d[81]), "+f"(d[82]), "+f"(d[83]),
          "+f"(d[84]), "+f"(d[85]), "+f"(d[86]), "+f"(d[87]), "+f"(d[88]), "+f"(d[89]), "+f"(d[90]), "+f"(d[91]), "+f"(d[92]), "+f"(d[93]), "+f"(d[94]), "+f"(d[95]),
          "+f"(d[96]), "+f"(d[97]), "+f"(d[98]), "+f"(d[99]), "+f"(d[100]), "+f"(d[101]), "+f"(d[102]), "+f"(d[103]), "+f"(d[104]), "+f"(d[105]), "+f"(d[106]), "+f"(d[107]),
          "+f"(d[108]), "+f"(d[109]), "+f"(d[110]), "+f"(d[111])
        : "r"(a[0]), "r"(a[1]), "r"(a[2]), "r"(a[3]), "l"(db));
}
__device__ __forceinline__ void wgmma_n224_init(float (&d)[112], const uint32_t (&a)[4], uint64_t db) {
    asm volatile("{.reg .pred p; setp.ne.b32 p, 0, 0;\n"
        "wgmma.mma_async.sync.aligned.m64n224k16.f32.bf16.bf16 {"
        "%0, %1, %2, %3, %4, %5, %6, %7, %8, %9, %10, %11, %12, %13, %14, %15, %16, %17, %18, %19, %20, %21, %22, %23, "
        "%24, %25, %26, %27, %28, %29, %30, %31, %32, %33, %34, %35, %36, %37, %38, %39, %40, %41, %42, %43, %44, %45, %46, %47, "
        "%48, %49, %50, %51, %52, %53, %54, %55, %56, %57, %58, %59, %60, %61, %62, %63, %64, %65, %66, %67, %68, %69, %70, %71, "
        "%72, %73, %74, %75, %76, %77, %78, %79, %80, %81, %82, %83, %84, %85, %86, %87, %88, %89, %90, %91, %92, %93, %94, %95, "
        "%96, %97, %98, %99, %100, %101, %102, %103, %104, %105, %106, %107, %108, %109, %110, %111"
        "}, {%112, %113, %114, %115}, %116, p, 1, 1, 1;}\n"
        : "=f"(d[0]), "=f"(d[1]), "=f"(d[2]), "=f"(d[3]), "=f"(d[4]), "=f"(d[5]), "=f"(d[6]), "=f"(d[7]), "=f"(d[8]), "=f"(d[9]), "=f"(d[10]), "=f"(d[11]),
          "=f"(d[12]), "=f"(d[13]), "=f"(d[14]), "=f"(d[15]), "=f"(d[16]), "=f"(d[17]), "=f"(d[18]), "=f"(d[19]), "=f"(d[20]), "=f"(d[21]), "=f"(d[22]), "=f"(d[23]),
          "=f"(d[24]), "=f"(d[25]), "=f"(d[26]), "=f"(d[27]), "=f"(d[28]), "=f"(d[29]), "=f"(d[30]), "=f"(d[31]), "=f"(d[32]), "=f"(d[33]), "=f"(d[34]), "=f"(d[35]),
          "=f"(d[36]), "=f"(d[37]), "=f"(d[38]), "=f"(d[39]), "=f"(d[40]), "=f"(d[41]), "=f"(d[42]), "=f"(d[43]), "=f"(d[44]), "=f"(d[45]), "=f"(d[46]), "=f"(d[47]),
          "=f"(d[48]), "=f"(d[49]), "=f"(d[50]), "=f"(d[51]), "=f"(d[52]), "=f"(d[53]), "=f"(d[54]), "=f"(d[55]), "=f"(d[56]), "=f"(d[57]), "=f"(d[58]), "=f"(d[59]),
          "=f"(d[60]), "=f"(d[61]), "=f"(d[62]), "=f"(d[63]), "=f"(d[64]), "=f"(d[65]), "=f"(d[66]), "=f"(d[67]), "=f"(d[68]), "=f"(d[69]), "=f"(d[70]), "=f"(d[71]),
          "=f"(d[72]), "=f"(d[73]), "=f"(d[74]), "=f"(d[75]), "=f"(d[76]), "=f"(d[77]), "=f"(d[78]), "=f"(d[79]), "=f"(d[80]), "=f"(d[81]), "=f"(d[82]), "=f"(d[83]),
          "=f"(d[84]), "=f"(d[85]), "=f"(d[86]), "=f"(d[87]), "=f"(d[88]), "=f"(d[89]), "=f"(d[90]), "=f"(d[91]), "=f"(d[92]), "=f"(d[93]), "=f"(d[94]), "=f"(d[95]),
          "=f"(d[96]), "=f"(d[97]), "=f"(d[98]), "=f"(d[99]), "=f"(d[100]), "=f"(d[101]), "=f"(d[102]), "=f"(d[103]), "=f"(d[104]), "=f"(d[105]), "=f"(d[106]), "=f"(d[107]),
          "=f"(d[108]), "=f"(d[109]), "=f"(d[110]), "=f"(d[111])
        : "r"(a[0]), "r"(a[1]), "r"(a[2]), "r"(a[3]), "l"(db));
}
__device__ __forceinline__ void wgmma_n80_acc(float (&d)[40], const uint32_t (&a)[4], uint64_t db) {
    asm volatile("{.reg .pred p; setp.eq.b32 p, 0, 0;\n"
        "wgmma.mma_async.sync.aligned.m64n80k16.f32.bf16.bf16 {"
        "%0, %1, %2, %3, %4, %5, %6, %7, %8, %9, %10, %11, %12, %13, %14, %15, %16, %17, %18, %19, %20, %21, %22, %23, "
        "%24, %25, %26, %27, %28, %29, %30, %31, %32, %33, %34, %35, %36, %37, %38, %39"
        "}, {%40, %41, %42, %43}, %44, p, 1, 1, 1;}\n"
        : "+f"(d[0]), "+f"(d[1]), "+f"(d[2]), "+f"(d[3]), "+f"(d[4]), "+f"(d[5]), "+f"(d[6]), "+f"(d[7]), "+f"(d[8]), "+f"(d[9]), "+f"(d[10]), "+f"(d[11]),
          "+f"(d[12]), "+f"(d[13]), "+f"(d[14]), "+f"(d[15]), "+f"(d[16]), "+f"(d[17]), "+f"(d[18]), "+f"(d[19]), "+f"(d[20]), "+f"(d[21]), "+f"(d[22]), "+f"(d[23]),
          "+f"(d[24]), "+f"(d[25]), "+f"(d[26]), "+f"(d[27]), "+f"(d[28]), "+f"(d[29]), "+f"(d[30]), "+f"(d[31]), "+f"(d[32]), "+f"(d[33]), "+f"(d[34]), "+f"(d[35]),
          "+f"(d[36]), "+f"(d[37]), "+f"(d[38]), "+f"(d[39])
        : "r"(a[0]), "r"(a[1]), "r"(a[2]), "r"(a[3]), "l"(db));
}
__device__ __forceinline__ void wgmma_n160_acc(float (&d)[80], const uint32_t (&a)[4], uint64_t db) {
    asm volatile("{.reg .pred p; setp.eq.b32 p, 0, 0;\n"
        "wgmma.mma_async.sync.aligned.m64n160k16.f32.bf16.bf16 {"
        "%0, %1, %2, %3, %4, %5, %6, %7, %8, %9, %10, %11, %12, %13, %14, %15, %16, %17, %18, %19, %20, %21, %22, %23, "
        "%24, %25, %26, %27, %28, %29, %30, %31, %32, %33, %34, %35, %36, %37, %38, %39, %40, %41, %42, %43, %44, %45, %46, %47, "
        "%48, %49, %50, %51, %52, %53, %54, %55, %56, %57, %58, %59, %60, %61, %62, %63, %64, %65, %66, %67, %68, %69, %70, %71, "
        "%72, %73, %74, %75, %76, %77, %78, %79"
        "}, {%80, %81, %82, %83}, %84, p, 1, 1, 1;}\n"
        : "+f"(d[0]), "+f"(d[1]), "+f"(d[2]), "+f"(d[3]), "+f"(d[4]), "+f"(d[5]), "+f"(d[6]), "+f"(d[7]), "+f"(d[8]), "+f"(d[9]), "+f"(d[10]), "+f"(d[11]),
          "+f"(d[12]), "+f"(d[13]), "+f"(d[14]), "+f"(d[15]), "+f"(d[16]), "+f"(d[17]), "+f"(d[18]), "+f"(d[19]), "+f"(d[20]), "+f"(d[21]), "+f"(d[22]), "+f"(d[23]),
          "+f"(d[24]), "+f"(d[25]), "+f"(d[26]), "+f"(d[27]), "+f"(d[28]), "+f"(d[29]), "+f"(d[30]), "+f"(d[31]), "+f"(d[32]), "+f"(d[33]), "+f"(d[34]), "+f"(d[35]),
          "+f"(d[36]), "+f"(d[37]), "+f"(d[38]), "+f"(d[39]), "+f"(d[40]), "+f"(d[41]), "+f"(d[42]), "+f"(d[43]), "+f"(d[44]), "+f"(d[45]), "+f"(d[46]), "+f"(d[47]),
          "+f"(d[48]), "+f"(d[49]), "+f"(d[50]), "+f"(d[51]), "+f"(d[52]), "+f"(d[53]), "+f"(d[54]), "+f"(d[55]), "+f"(d[56]), "+f"(d[57]), "+f"(d[58]), "+f"(d[59]),
          "+f"(d[60]), "+f"(d[61]), "+f"(d[62]), "+f"(d[63]), "+f"(d[64]), "+f"(d[65]), "+f"(d[66]), "+f"(d[67]), "+f"(d[68]), "+f"(d[69]), "+f"(d[70]), "+f"(d[71]),
          "+f"(d[72]), "+f"(d[73]), "+f"(d[74]), "+f"(d[75]), "+f"(d[76]), "+f"(d[77]), "+f"(d[78]), "+f"(d[79])
        : "r"(a[0]), "r"(a[1]), "r"(a[2]), "r"(a[3]), "l"(db));
}
__device__ __forceinline__ void wgmma_n160_init(float (&d)[80], const uint32_t (&a)[4], uint64_t db) {
    asm volatile("{.reg .pred p; setp.ne.b32 p, 0, 0;\n"
        "wgmma.mma_async.sync.aligned.m64n160k16.f32.bf16.bf16 {"
        "%0, %1, %2, %3, %4, %5, %6, %7, %8, %9, %10, %11, %12, %13, %14, %15, %16, %17, %18, %19, %20, %21, %22, %23, "
        "%24, %25, %26, %27, %28, %29, %30, %31, %32, %33, %34, %35, %36, %37, %38, %39, %40, %41, %42, %43, %44, %45, %46, %47, "
        "%48, %49, %50, %51, %52, %53, %54, %55, %56, %57, %58, %59, %60, %61, %62, %63, %64, %65, %66, %67, %68, %69, %70, %71, "
        "%72, %73, %74, %75, %76, %77, %78, %79"
        "}, {%80, %81, %82, %83}, %84, p, 1, 1, 1;}\n"
        : "=f"(d[0]), "=f"(d[1]), "=f"(d[2]), "=f"(d[3]), "=f"(d[4]), "=f"(d[5]), "=f"(d[6]), "=f"(d[7]), "=f"(d[8]), "=f"(d[9]), "=f"(d[10]), "=f"(d[11]),
          "=f"(d[12]), "=f"(d[13]), "=f"(d[14]), "=f"(d[15]), "=f"(d[16]), "=f"(d[17]), "=f"(d[18]), "=f"(d[19]), "=f"(d[20]), "=f"(d[21]), "=f"(d[22]), "=f"(d[23]),
          "=f"(d[24]), "=f"(d[25]), "=f"(d[26]), "=f"(d[27]), "=f"(d[28]), "=f"(d[29]), "=f"(d[30]), "=f"(d[31]), "=f"(d[32]), "=f"(d[33]), "=f"(d[34]), "=f"(d[35]),
          "=f"(d[36]), "=f"(d[37]), "=f"(d[38]), "=f"(d[39]), "=f"(d[40]), "=f"(d[41]), "=f"(d[42]), "=f"(d[43]), "=f"(d[44]), "=f"(d[45]), "=f"(d[46]), "=f"(d[47]),
          "=f"(d[48]), "=f"(d[49]), "=f"(d[50]), "=f"(d[51]), "=f"(d[52]), "=f"(d[53]), "=f"(d[54]), "=f"(d[55]), "=f"(d[56]), "=f"(d[57]), "=f"(d[58]), "=f"(d[59]),
          "=f"(d[60]), "=f"(d[61]), "=f"(d[62]), "=f"(d[63]), "=f"(d[64]), "=f"(d[65]), "=f"(d[66]), "=f"(d[67]), "=f"(d[68]), "=f"(d[69]), "=f"(d[70]), "=f"(d[71]),
          "=f"(d[72]), "=f"(d[73]), "=f"(d[74]), "=f"(d[75]), "=f"(d[76]), "=f"(d[77]), "=f"(d[78]), "=f"(d[79])
        : "r"(a[0]), "r"(a[1]), "r"(a[2]), "r"(a[3]), "l"(db));
}
__device__ __forceinline__ void wgmma_n128_acc(float (&d)[64], const uint32_t (&a)[4], uint64_t db) {
    asm volatile("{.reg .pred p; setp.eq.b32 p, 0, 0;\n"
        "wgmma.mma_async.sync.aligned.m64n128k16.f32.bf16.bf16 {"
        "%0, %1, %2, %3, %4, %5, %6, %7, %8, %9, %10, %11, %12, %13, %14, %15, %16, %17, %18, %19, %20, %21, %22, %23, "
        "%24, %25, %26, %27, %28, %29, %30, %31, %32, %33, %34, %35, %36, %37, %38, %39, %40, %41, %42, %43, %44, %45, %46, %47, "
        "%48, %49, %50, %51, %52, %53, %54, %55, %56, %57, %58, %59, %60, %61, %62, %63"
        "}, {%64, %65, %66, %67}, %68, p, 1, 1, 1;}\n"
        : "+f"(d[0]), "+f"(d[1]), "+f"(d[2]), "+f"(d[3]), "+f"(d[4]), "+f"(d[5]), "+f"(d[6]), "+f"(d[7]), "+f"(d[8]), "+f"(d[9]), "+f"(d[10]), "+f"(d[11]),
          "+f"(d[12]), "+f"(d[13]), "+f"(d[14]), "+f"(d[15]), "+f"(d[16]), "+f"(d[17]), "+f"(d[18]), "+f"(d[19]), "+f"(d[20]), "+f"(d[21]), "+f"(d[22]), "+f"(d[23]),
          "+f"(d[24]), "+f"(d[25]), "+f"(d[26]), "+f"(d[27]), "+f"(d[28]), "+f"(d[29]), "+f"(d[30]), "+f"(d[31]), "+f"(d[32]), "+f"(d[33]), "+f"(d[34]), "+f"(d[35]),
          "+f"(d[36]), "+f"(d[37]), "+f"(d[38]), "+f"(d[39]), "+f"(d[40]), "+f"(d[41]), "+f"(d[42]), "+f"(d[43]), "+f"(d[44]), "+f"(d[45]), "+f"(d[46]), "+f"(d[47]),
          "+f"(d[48]), "+f"(d[49]), "+f"(d[50]), "+f"(d[51]), "+f"(d[52]), "+f"(d[53]), "+f"(d[54]), "+f"(d[55]), "+f"(d[56]), "+f"(d[57]), "+f"(d[58]), "+f"(d[59]),
          "+f"(d[60]), "+f"(d[61]), "+f"(d[62]), "+f"(d[63])
        : "r"(a[0]), "r"(a[1]), "r"(a[2]), "r"(a[3]), "l"(db));
}
__device__ __forceinline__ void wgmma_n96_acc(float (&d)[48], const uint32_t (&a)[4], uint64_t db) {
    asm volatile("{.reg .pred p; setp.eq.b32 p, 0, 0;\n"
        "wgmma.mma_async.sync.aligned.m64n96k16.f32.bf16.bf16 {"
        "%0, %1, %2, %3, %4, %5, %6, %7, %8, %9, %10, %11, %12, %13, %14, %15, %16, %17, %18, %19, %20, %21, %22, %23, "
        "%24, %25, %26, %27, %28, %29, %30, %31, %32, %33, %34, %35, %36, %37, %38, %39, %40, %41, %42, %43, %44, %45, %46, %47"
        "}, {%48, %49, %50, %51}, %52, p, 1, 1, 1;}\n"
        : "+f"(d[0]), "+f"(d[1]), "+f"(d[2]), "+f"(d[3]), "+f"(d[4]), "+f"(d[5]), "+f"(d[6]), "+f"(d[7]), "+f"(d[8]), "+f"(d[9]), "+f"(d[10]), "+f"(d[11]),
          "+f"(d[12]), "+f"(d[13]), "+f"(d[14]), "+f"(d[15]), "+f"(d[16]), "+f"(d[17]), "+f"(d[18]), "+f"(d[19]), "+f"(d[20]), "+f"(d[21]), "+f"(d[22]), "+f"(d[23]),
          "+f"(d[24]), "+f"(d[25]), "+f"(d[26]), "+f"(d[27]), "+f"(d[28]), "+f"(d[29]), "+f"(d[30]), "+f"(d[31]), "+f"(d[32]), "+f"(d[33]), "+f"(d[34]), "+f"(d[35]),
          "+f"(d[36]), "+f"(d[37]), "+f"(d[38]), "+f"(d[39]), "+f"(d[40]), "+f"(d[41]), "+f"(d[42]), "+f"(d[43]), "+f"(d[44]), "+f"(d[45]), "+f"(d[46]), "+f"(d[47])
        : "r"(a[0]), "r"(a[1]), "r"(a[2]), "r"(a[3]), "l"(db));
}
__device__ __forceinline__ void wgmma_n64_acc(float (&d)[32], const uint32_t (&a)[4], uint64_t db) {
    asm volatile("{.reg .pred p; setp.eq.b32 p, 0, 0;\n"
        "wgmma.mma_async.sync.aligned.m64n64k16.f32.bf16.bf16 {"
        "%0, %1, %2, %3, %4, %5, %6, %7, %8, %9, %10, %11, %12, %13, %14, %15, %16, %17, %18, %19, %20, %21, %22, %23, "
        "%24, %25, %26, %27, %28, %29, %30, %31"
        "}, {%32, %33, %34, %35}, %36, p, 1, 1, 1;}\n"
        : "+f"(d[0]), "+f"(d[1]), "+f"(d[2]), "+f"(d[3]), "+f"(d[4]), "+f"(d[5]), "+f"(d[6]), "+f"(d[7]), "+f"(d[8]), "+f"(d[9]), "+f"(d[10]), "+f"(d[11]),
          "+f"(d[12]), "+f"(d[13]), "+f"(d[14]), "+f"(d[15]), "+f"(d[16]), "+f"(d[17]), "+f"(d[18]), "+f"(d[19]), "+f"(d[20]), "+f"(d[21]), "+f"(d[22]), "+f"(d[23]),
          "+f"(d[24]), "+f"(d[25]), "+f"(d[26]), "+f"(d[27]), "+f"(d[28]), "+f"(d[29]), "+f"(d[30]), "+f"(d[31])
        : "r"(a[0]), "r"(a[1]), "r"(a[2]), "r"(a[3]), "l"(db));
}

__device__ __forceinline__ int slice_at(int t, int r) { return t < 2 ? r ^ t : (t - 2) + ((t - 2) >= (r & 6) ? 2 : 0); }

__device__ __forceinline__ int hsrc_at(int t, int r) {
    if (t < 2) return r;
    const int i = t < 5 ? t - 2 : t - 5;
    return 2 * (i + (i >= (r >> 1) ? 1 : 0)) + (r & 1);
}
__device__ __forceinline__ constexpr bool hpartB(int t) { return t == 1 || t >= 5; }
__device__ __forceinline__ int main_col(int j) { return 80 * j + 16 * (j & 1); }
__device__ __forceinline__ int rem_col(int j) { return 80 * j + 64 - 64 * (j & 1); }

template <int NV> __device__ __forceinline__ void ld_vecs(uint32_t (&v)[NV][4], const char* p) {
#pragma unroll
    for (int u = 0; u < NV; u++) ldv(v[u], p + u * 512);
}
template <int NV> __device__ __forceinline__ bool bad_vecs(const uint32_t (&v)[NV][4], uint32_t tag) {
    uint32_t bad = 0;
#pragma unroll
    for (int u = 0; u < NV; u += 2) {
        if (u + 1 < NV) {
            uint32_t x;
            asm("lop3.b32 %0, %1, %2, %3, 0x7e;" : "=r"(x) : "r"(v[u][0]), "r"(v[u + 1][0]), "r"(tag));
            bad |= x;
        } else {
            asm("lop3.b32 %0, %1, %2, %0, 0xbe;" : "+r"(bad) : "r"(v[u][0]), "r"(tag));
        }
    }
    return __any_sync(0xffffffffu, bad & 1);
}
struct Ctx {
    uint32_t sb, sb16;
    uint32_t rel_addr;
    uint32_t wl;
    const Params* prm;
    int r, warp;
    int budget;
    int never;
    uint32_t ord;
    uint32_t pr[8];
    __device__ __forceinline__ int lane16() const { return launder(wl) - warp * 2560; }
    __device__ __forceinline__ int lane() const { return (uint32_t)lane16() >> 4; }
    __device__ __forceinline__ uint32_t park() const { return sb + OFF_PARK + launder(wl); }
};
__device__ __forceinline__ void sched_fence(Ctx& c) {
    asm volatile("{.reg .pred p; setp.eq.s32 p, %0, 0x4%=;\nFENCE_%=: @p nanosleep.u32 1; @p bra.uni FENCE_%=;}" :: "r"(c.never) : "memory");
}
template <int K> __device__ __forceinline__ void order_wait(Ctx& c) {
    if ((ORDER >> K) & 1) { if (c.warp >= 4) mbar_wait0(c.ord + K * 8, c.budget); }
}
template <int K> __device__ __forceinline__ void order_post(const Ctx& c) {
    if ((ORDER >> K) & 1) { if (c.wl == 0) mbar_arrive(c.ord + K * 8); }
}
template <int NV, int STRIDE = 512, class F> __device__ __forceinline__ void check_vecs(Ctx& c, uint32_t (&v)[NV][4], uint32_t tag, F off) {
    sched_fence(c);
    while (bad_vecs(v, tag) && --c.budget >= 0) {
        const char* p = c.prm->scr + off();
#pragma unroll
        for (int u = 0; u < NV; u++) ldv(v[u], p + u * STRIDE);
    }
}
__device__ __forceinline__ void wait_full(Ctx& c, int item) { mbar_wait0(c.sb + BAR_FULL + item * 8, c.budget); }
__device__ __forceinline__ void release(const Ctx& c, int item) {
    if ((c.prm->item[item] >> 24) && c.rel_addr != 0) mbar_arrive_cluster(c.rel_addr + item * 8);
}
__device__ __forceinline__ uint32_t item16(const Ctx& c, int item) { return c.sb16 + (c.prm->item[item] & 0xffffu); }
__device__ __forceinline__ uint32_t slab_off(const Ctx& c, int idx) { return launder(idx) * SLAB + launder(c.wl); }
__device__ __forceinline__ char* slab(const Ctx& c, int idx) { return c.prm->scr + slab_off(c, idx); }
__device__ __forceinline__ void sts5(uint32_t a, const uint32_t (&v)[5][4]) {
#pragma unroll
    for (int u = 0; u < 5; u++)
        asm volatile("st.shared.v4.u32 [%0], {%1,%2,%3,%4};" :: "r"(a + u * 512), "r"(v[u][0]), "r"(v[u][1]), "r"(v[u][2]), "r"(v[u][3]) : "memory");
}
template <int NV> __device__ __forceinline__ void lds5(uint32_t (&v)[NV][4], uint32_t a) {
#pragma unroll
    for (int u = 0; u < 5; u++)
        asm volatile("ld.shared.v4.u32 {%0,%1,%2,%3}, [%4];" : "=r"(v[u][0]), "=r"(v[u][1]), "=r"(v[u][2]), "=r"(v[u][3]) : "r"(a + u * 512) : "memory");
}

__device__ __forceinline__ void park_x(uint32_t a, const uint32_t (&v)[5][4]) {
#pragma unroll
    for (int u = 0; u < 5; u++)
        asm volatile("stmatrix.sync.aligned.m8n8.x4.shared.b16 [%0], {%1,%2,%3,%4};" :: "r"(a + u * 512), "r"(v[u][0]), "r"(v[u][1]), "r"(v[u][2]), "r"(v[u][3]) : "memory");
}
__device__ __forceinline__ void unpark_x(uint32_t (&v)[5][4], uint32_t a) {
#pragma unroll
    for (int u = 0; u < 5; u++)
        asm volatile("ldmatrix.sync.aligned.m8n8.x4.shared.b16 {%0,%1,%2,%3}, [%4];" : "=r"(v[u][0]), "=r"(v[u][1]), "=r"(v[u][2]), "=r"(v[u][3]) : "r"(a + u * 512) : "memory");
}
__device__ __forceinline__ void ldsm4(uint32_t (&v)[4], uint32_t a) {
    asm volatile("ldmatrix.sync.aligned.m8n8.x4.shared.b16 {%0,%1,%2,%3}, [%4];" : "=r"(v[0]), "=r"(v[1]), "=r"(v[2]), "=r"(v[3]) : "r"(a) : "memory");
}
__device__ __forceinline__ uint32_t stage_addr(uint32_t sb, int warp, int lane) { return sb + STAGE_OFF + (warp * 16 + (lane & 15)) * 336 + (lane >> 4) * 16; }
__device__ __forceinline__ int tile_goff(int i, int r, int lane) {
    if (i < 4) return 2 * ((lane & 7) + 8 * (i & 1)) * DM + main_col(r) + 32 * (i >> 1) + 8 * (lane >> 3);
    return 2 * (lane & 15) * DM + rem_col(r) + 8 * (lane >> 4);
}
__device__ __forceinline__ int tile_soff(int i, int lane) {
    if (i < 4) return (2 * (i >> 1) + (lane >> 4)) * 512 + (((lane >> 3) & 1) * 2 + (i & 1)) * 128 + (lane & 7) * 16;
    return 2048 + lane * 16;
}

template <int N, int OFF, int TOT> __device__ __forceinline__ void rename(float (&d)[N], const float (&s)[TOT]) {
#pragma unroll
    for (int i = 0; i < N; i++) asm volatile("mov.f32 %0, %1;" : "=f"(d[i]) : "f"(s[OFF + i]));
}

__device__ __forceinline__ int kstep(int j, int u) { return u < 4 ? (j & 1) + u : 4 - 4 * (j & 1); }

struct GQKV {
    float m[96], r[24];
    static constexpr int SPI = 1;
    template <bool INIT> __device__ __forceinline__ void step(const uint32_t (&a)[5][4], uint32_t base, int, int j) {
#pragma unroll
        for (int u = 0; u < 5; u++) {
            uint64_t dm = mkdesc(base + kstep(j, u) * 128, 0, 10240, 1024, 1), dr = mkdesc(base + kstep(j, u) * 32, 30720, 2560, 256, 3);
            if (INIT && u == 0) { wgmma_n192_init(m, a[u], dm); wgmma_n48_init(r, a[u], dr); }
            else { wgmma_n192_acc(m, a[u], dm); wgmma_n48_acc(r, a[u], dr); }
        }
    }
};
struct GW1 {
    float m[112];
    static constexpr int SPI = 1;
    template <bool INIT> __device__ __forceinline__ void step(const uint32_t (&a)[5][4], uint32_t base, int, int j) {
#pragma unroll
        for (int u = 0; u < 5; u++) {
            uint64_t d = mkdesc(base + kstep(j, u) * 64, 0, 5120, 512, 2);
            if (INIT && u == 0) wgmma_n224_init(m, a[u], d); else wgmma_n224_acc(m, a[u], d);
        }
    }
};
struct GWO {
    float m[40];
    static constexpr int SPI = 2;
    template <bool INIT> __device__ __forceinline__ void step(const uint32_t (&a)[5][4], uint32_t base, int sub, int) {
#pragma unroll
        for (int u = 0; u < 5; u++) wgmma_n80_acc(m, a[u], mkdesc(base, sub * 15360 + u * 1024, 5120, 512, 2));
    }
};

__device__ __forceinline__ void publish_x(const Ctx& c, uint32_t (&X)[5][4], int slab_idx, uint32_t tag, bool park = true) {
    if (park) park_x(c.park(), X);
    char* agp = slab(c, slab_idx);
    char* agm = agp + (c.r & 1) * 512;
#pragma unroll
    for (int u = 0; u < 5; u++) {
        X[u][0] = launder(tagged(X[u][0], tag));
        stv(u < 4 ? agm + u * 512 : agp + kstep(c.r, 4) * 512, X[u][0], X[u][1], X[u][2], X[u][3]);
    }
}
__device__ __forceinline__ void local_stats(float (&s)[4], const float (&v)[40]) {
    s[0] = 0.f; s[1] = 0.f; s[2] = 0.f; s[3] = 0.f;
#pragma unroll
    for (int j = 0; j < 10; j++) {
        s[0] += v[4 * j] + v[4 * j + 1];
        s[1] = fmaf(v[4 * j], v[4 * j], fmaf(v[4 * j + 1], v[4 * j + 1], s[1]));
        s[2] += v[4 * j + 2] + v[4 * j + 3];
        s[3] = fmaf(v[4 * j + 2], v[4 * j + 2], fmaf(v[4 * j + 3], v[4 * j + 3], s[3]));
    }
}
__device__ __forceinline__ void publish_stats(const Ctx& c, float (&s)[4], uint32_t stoff, uint32_t tag) {
#pragma unroll
    for (int i = 0; i < 4; i++) {
        s[i] += __shfl_xor_sync(0xffffffffu, s[i], 1);
        s[i] += __shfl_xor_sync(0xffffffffu, s[i], 2);
    }
    char* stp = c.prm->scr + (uint32_t)(G_XST + stoff + c.r * 1024 + c.lane() * 4);
    if ((c.lane() & 3) == 0) stv(stp, tagged(__float_as_uint(s[0]), tag), __float_as_uint(s[1]), __float_as_uint(s[2]), __float_as_uint(s[3]));
}

template <int NB> struct Gather {
    uint32_t buf[NB][5][4];
    int slab0;
    uint32_t tag;
    __device__ __forceinline__ uint32_t (&at(int t))[5][4] { return buf[(t - 1) % NB]; }
    __device__ __forceinline__ void fetch(Ctx& c, int t) { ld_vecs(at(t), slab(c, slab0 + slice_at(t, c.r))); }
    __device__ __forceinline__ void check(Ctx& c, int t) { check_vecs(c, at(t), tag, [&]() { return slab_off(c, slab0 + slice_at(t, c.r)); }); }
};
struct Stats {
    uint32_t v[2][4];
    __device__ __forceinline__ uint32_t off(const Ctx& c, uint32_t stoff) { return G_XST + stoff + (c.lane() & 3) * 1024 + (c.lane() >> 2) * 16; }
    __device__ __forceinline__ void fetch(const Ctx& c, uint32_t stoff) {
        const char* st = c.prm->scr + off(c, stoff);
        ldv(v[0], st); ldv(v[1], st + 4096);
    }
    __device__ __forceinline__ void check(Ctx& c, uint32_t stoff, uint32_t tag) { check_vecs<2, 4096>(c, v, tag, [&]() { return off(c, stoff); }); }
    __device__ __forceinline__ void finish(const Ctx& c, float& rsA, float& rsB, uint32_t (&ax)[4]) {
        float s[4];
#pragma unroll
        for (int i = 0; i < 4; i++) {
            s[i] = __uint_as_float(v[0][i]) + __uint_as_float(v[1][i]);
            s[i] += __shfl_xor_sync(0xffffffffu, s[i], 1);
            s[i] += __shfl_xor_sync(0xffffffffu, s[i], 2);
        }
        const float mA = s[0] * (1.f / DM), mB = s[2] * (1.f / DM);
        rsA = rsqrtf(fmaxf(fmaf(-mA, mA, s[1] * (1.f / DM)), 0.f) + LN_EPS);
        rsB = rsqrtf(fmaxf(fmaf(-mB, mB, s[3] * (1.f / DM)), 0.f) + LN_EPS);
        const uint32_t h = pack2(mA, mB);
        const uint32_t l = pack2(mA - bf_lo(h), mB - bf_hi(h));
        const bool on = (c.lane() & 2) == 0;
        ax[0] = on ? __byte_perm(h, l, 0x5410) : 0u;
        ax[1] = on ? __byte_perm(h, l, 0x7632) : 0u;
        ax[2] = 0u; ax[3] = 0u;
        asm volatile("" : "+r"(ax[2]), "+r"(ax[3]));
    }
};
template <class G, int LAST, int O0, class Hook>
__device__ __forceinline__ void ln_head(G& g, Gather<3>& a, Ctx& c, int item0, const uint32_t (&own)[5][4], const float (&xv)[40],
                                        uint32_t stoff, float& rsA, float& rsB, uint32_t (&ax)[4], Hook hook, int role, int tl0, bool pron) {
    Stats sv;
    PR(pron, 0);
    sched_fence(c);
    order_wait<O0>(c);
    wg_fence();
    g.template step<true>(own, item16(c, item0), 0, c.r);
    wg_commit();
    order_post<O0>(c);
    PR(pron, 1);
    if (tl0) TL(tl0 + 1);
    PRB(pron, 7);
    sched_fence(c);
    hook(-1);
    PR(pron, 2);
    if (tl0) TL(tl0 + 2);
    wait_full(c, item0 + 1);
    PR(pron, 3);
    float ls[4];
    local_stats(ls, xv);
    sched_fence(c);
    PR(pron, 4);
    hook(0);
    a.check(c, 1);
    PR(pron, 5);
    if (PROBE && pron) c.pr[7] -= c.budget;
    a.fetch(c, 2);
#pragma unroll
    for (int t = 1; t <= LAST; t++) {
        if (t > 1) wait_full(c, item0 + t); else sched_fence(c);
        if (tl0) TL(tl0 + 2 + t);
        if (t == 1) order_wait<O0 + 1>(c);
        wg_fence();
        g.template step<false>(a.at(t), item16(c, item0 + t), 0, 0);
        wg_commit();
        if (t == 1) order_post<O0 + 1>(c);
        if (t == 1) PR(pron, 6);
        if (t == 2) PRDUMP(pron);
        if (t == 1) { sched_fence(c); publish_stats(c, ls, stoff, a.tag); }
        wg_wait<1>();
        release(c, item0 + t - 1);
        a.check(c, t + 1);
        if (t == LAST) sv.check(c, stoff, a.tag);
        a.fetch(c, t + 2);
        if (t == LAST - 1) sv.fetch(c, stoff);
        hook(t);
    }
    sched_fence(c);
    sv.finish(c, rsA, rsB, ax);
}

__device__ __forceinline__ void pack_x(uint32_t (&X)[5][4], const float (&v)[40]) {
#pragma unroll
    for (int u = 0; u < 5; u++)
#pragma unroll
        for (int i = 0; i < 4; i++) X[u][i] = pack2(v[8 * u + 2 * i], v[8 * u + 2 * i + 1]);
}
__device__ __forceinline__ void unpack_x(float (&v)[40], const uint32_t (&X)[5][4]) {
#pragma unroll
    for (int u = 0; u < 5; u++)
#pragma unroll
        for (int i = 0; i < 4; i++) { v[8 * u + 2 * i] = bf_lo(X[u][i]); v[8 * u + 2 * i + 1] = bf_hi(X[u][i]); }
}
__device__ __forceinline__ void store_out(const Ctx& c, const uint32_t (&X)[5][4], __nv_bfloat16* out) {
    park_x(c.park(), X);
    __syncwarp();
    const uint32_t slot = c.sb + OFF_PARK + c.warp * 2560;
    const int lane = c.lane();
#pragma unroll
    for (int i = 0; i < 5; i++) {
        uint4 v;
        asm volatile("ld.shared.v4.u32 {%0,%1,%2,%3}, [%4];" : "=r"(v.x), "=r"(v.y), "=r"(v.z), "=r"(v.w) : "r"(slot + tile_soff(i, lane)) : "memory");
        *reinterpret_cast<uint4*>(out + tile_goff(i, c.r, lane)) = v;
    }
    __syncwarp();
}

__global__ void __cluster_dims__(2, 1, 1) __launch_bounds__(384, 1)
fused_layers_kernel(const __grid_constant__ Params prm, const __grid_constant__ CUtensorMap tmQM, const __grid_constant__ CUtensorMap tmQR,
                    const __grid_constant__ CUtensorMap tmWO, const __grid_constant__ CUtensorMap tmW1a, const __grid_constant__ CUtensorMap tmW1b,
                    const __grid_constant__ CUtensorMap tmW2, const __grid_constant__ CUtensorMap tmW2a) {
    extern __shared__ __align__(1024) uint8_t smem_raw[];
    const uint32_t sb = smem_u32(smem_raw);
    if (threadIdx.x == 256) {
        asm volatile("prefetch.tensormap [%0];" :: "l"(&tmQM) : "memory");
        asm volatile("prefetch.tensormap [%0];" :: "l"(&tmQR) : "memory");
        if (BPF & 1) l2_prefetch(prm.wqkv + blockIdx.x * (DM * DQKV / 128), DM * DQKV / 64);
    }
    const int warp = __shfl_sync(0xffffffffu, threadIdx.x >> 5, 0);
    const int lane = threadIdx.x & 31;
    const int cl = prm.role[blockIdx.x >> 1], p = blockIdx.x & 1;
    const int r = cl & 7, blk = (cl >> 3) * 2 + p;
    const int role = blk * 8 + r;
    TL(0); TLINIT

    auto produce = [&](int i) {
        const int k = i >= NITEMS_L ? i - NITEMS_L : i;
        const uint32_t base = sb + ((prm.item[i] & 0xffffu) << 4), bar = sb + BAR_FULL + i * 8;
        const int q = (k + p) & 1;
        if (k < 8) {
            const int np = k < 5 ? 3 : 2, row = 80 * slice_at(k, r), col = main_col(r) + 640 * (3 - np);
            mbar_expect(bar, np * 10240 + 7680);
            if (q) {
                tma2d_mc(base, &tmQM, col, row, bar);
                tma2d_mc(base + 10240, &tmQM, col + 640, row, bar);
            } else {
                if (np == 3) tma2d_mc(base + 20480, &tmQM, col + 1280, row, bar);
                tma3d_mc(base + np * 10240, &tmQR, rem_col(r), row, 0, bar);
            }
        } else if (k == 8) {
            mbar_expect(bar, 30720);
            tma2d_mc(base + q * 10240, &tmQM, main_col(r), 80 * slice_at(5 + q, r), bar);
            if (!q) tma2d_mc(base + 20480, &tmQM, main_col(r), 80 * slice_at(7, r), bar);
        } else if (k < IT_W1) {
            mbar_expect(bar, 30720);
            const int row = 80 * slice_at(2 * (k - IT_WO) + p, r);
#pragma unroll
            for (int a = 0; a < 3; a++) tma2d_mc(base + p * 15360 + a * 5120, &tmWO, a < 2 ? main_col(r) + 32 * a : rem_col(r), row, bar);
        } else if (k < IT_W2) {
            const bool full = k < IT_W1 + 6, pb = full ? q : k == IT_W1 + 7;
            mbar_expect(bar, full ? 35840 : pb ? 40960 : 30720);
            const int row = 80 * slice_at(full ? k - IT_W1 : 6 + p, r);
            if (pb) tma3d_mc(base + (full ? 0 : p * 20480), &tmW1b, 0, row, 7 * r, bar);
            else tma3d_mc(base + (full ? 20480 : p * 15360), &tmW1a, 0, row, 7 * r + 4, bar);
        } else if (k < IT_W2 + 8) {
            const int st = k - IT_W2, a0 = st < 6 ? 0 : 2;
            const bool pb = hpartB(st);
            const int atom = pb ? 8192 : 6144;
            mbar_expect(bar, (5 - a0) * atom);
            const int row = 224 * hsrc_at(st, r) + (pb ? 0 : 128);
#pragma unroll
            for (int a = 0; a < 5; a++)
                if (a >= a0 && (a & 1) == q)
                    tma2d_mc(base + (a - a0) * atom, pb ? &tmW2 : &tmW2a, a < 4 ? main_col(r ^ (a >> 1)) + 32 * (a & 1) : 160 * (r >> 1) + 64, row, bar);
        } else {
            mbar_expect(bar, 32768);
            const int row = 224 * hsrc_at(6 + p, r);
            tma2d_mc(base + p * 16384, &tmW2, main_col(r), row, bar);
            tma2d_mc(base + p * 16384 + 8192, &tmW2, main_col(r) + 32, row, bar);
        }
    };
    auto prefetch_w = [&](int t, int piece) {
        const char* wp = reinterpret_cast<const char*>(prm.wqkv + (size_t)(80 * slice_at(t, r) + 5 * blk + lane / 5) * DQKV + 640 * piece + 80 * r);
        if (lane < 25) asm volatile("prefetch.global.L2 [%0];" :: "l"(wp + (lane % 5) * 32));
    };
    uint32_t etag0 = 0;
    if (warp > 8 && elect_one()) {
#pragma unroll
        for (int i = 0; i < NITEMS / 3; i++) {
            mbar_init(sb + BAR_FULL + ((warp - 9) * (NITEMS / 3) + i) * 8, 1);
            mbar_init(sb + BAR_EMPTY + ((warp - 9) * (NITEMS / 3) + i) * 8, 16);
        }
        if (warp >= 10) mbar_init(sb + BAR_CS + (warp - 10) * 8, 3);
#pragma unroll
        for (int i = 0; i < 2 * NORD / 3; i++) mbar_init(sb + BAR_ORD + ((warp - 9) * (2 * NORD / 3) + i) * 8, 1);
        asm volatile("fence.mbarrier_init.release.cluster;" ::: "memory");
    }
    __syncwarp();
    asm volatile("barrier.cluster.arrive.relaxed.aligned;" ::: "memory");
    if (warp < 8) {
        const char* xr = reinterpret_cast<const char*>(prm.xin + (size_t)(128 * blk + 32 * (warp & 3) + (warp >> 2)) * DM + 160 * (r >> 1)) + lane * 16;
        if (lane < 20) {
#pragma unroll
            for (int i = 0; i < 16; i++)
                asm volatile("cp.async.cg.shared.global [%0], [%1], 16;" :: "r"(sb + STAGE_OFF + (warp * 16 + i) * 336 + lane * 16), "l"(xr + i * 4 * DM) : "memory");
        }
        etag0 = __ldcg(reinterpret_cast<const unsigned*>(prm.scr + G_EPOCH + role * 128) + lane);
    } else if (warp > 8) {
        etag0 = __ldcg(reinterpret_cast<const unsigned*>(prm.scr + G_EPOCH + role * 128) + lane);
#pragma unroll 1
        for (int t = 0; t < PF_STEPS; t++) prefetch_w(t, warp - 9);
    }
    TL(10);
    asm volatile("barrier.cluster.wait.aligned;" ::: "memory");
    if (warp == 8) {
        TL(1);
        if (elect_one()) {
#pragma unroll 1
            for (int i = 0; i < NOMC; i++) {
                const uint32_t base = sb + ((prm.item[i] & 0xffffu) << 4), bar = sb + BAR_FULL + i * 8;
                const int row = 80 * slice_at(i, r);
                mbar_expect(bar, 38400);
                tma2d_mc(base + p * 10240, &tmQM, main_col(r) + 640 * p, row, bar);
                if (p) tma2d_mc(base + 20480, &tmQM, main_col(r) + 1280, row, bar);
                else tma3d_mc(base + 30720, &tmQR, rem_col(r), row, 0, bar);
            }
        }
        __syncwarp();
        TL(2);
    }

    if (warp < 8) {
        uint32_t X[5][4];
        float xv[40];
        Ctx c;
        c.sb = sb; c.sb16 = (sb & 0x3FFFF) >> 4; c.r = r; c.warp = warp; c.budget = SPIN_BUDGET; c.never = prm.minus1;
        c.prm = &prm;
        TL(11);
        asm volatile("cp.async.wait_all;" ::: "memory");
        TL(12);
        const uint32_t etag = __shfl_sync(0xffffffffu, (etag0 & 1u) ^ 1u, 0);
        __syncwarp();
        asm volatile("setmaxnreg.inc.sync.aligned.u32 %0;" :: "n"(REG_CONS));
        TL(14);
        {
            const uint32_t a = stage_addr(sb, warp, lane) + (r & 1) * 192;
#pragma unroll
            for (int u = 0; u < 5; u++) ldsm4(X[u], u < 4 ? a + u * 32 : a + 128 - (r & 1) * 160);
        }
        c.wl = __shfl_sync(0xffffffffu, warp * 2560 + lane * 16, lane);
        asm volatile("mapa.shared::cluster.u32 %0, %1, %2;" : "=r"(c.rel_addr) : "r"(sb + BAR_EMPTY), "r"(lane & 1));
        c.rel_addr = __shfl_sync(0xffffffffu, lane < 2 ? c.rel_addr : 0, lane);

        wait_full(c, 0);
        TL(13);
        unpack_x(xv, X);
        park_x(c.park(), X);
        TL(1);

        const int r_ = r, blk_ = blk, warp_ = warp;
#define PHASE_IDS const int r = launder(r_), blk = launder(blk_), warp = launder(warp_), role = blk * 8 + r, wg = warp >> 2, w = warp & 3; \
                  const uint32_t stoff = (blk * 64 + warp) * 128; c.r = r; c.warp = warp; (void)role; (void)wg; (void)w; (void)stoff;
#pragma unroll 1
        for (int layer = 0; layer < 2; layer++) {
            const int item0 = layer * NITEMS_L;
            c.ord = sb + BAR_ORD + layer * NORD * 8;
            const uint32_t ltag = layer ^ 1u;
            float rsA, rsB;
            uint32_t O[5][4];
            {
                PHASE_IDS
                GQKV q;
                Gather<3> ga;
                ga.slab0 = EX_X + blk * 8; ga.tag = 1u;
                uint32_t ax[4];
                auto clear_boxes = [&](int st) {
                    if (st == -1) {
                        if (layer == 0) {
                            const uint32_t a = stage_addr(sb, warp, c.lane()) + 160 - (r & 1) * 160;
#pragma unroll
                            for (int u = 0; u < 5; u++) ldsm4(ga.buf[0][u], a + u * 32);
#pragma unroll
                            for (int u = 0; u < 5; u++) ga.buf[0][u][0] |= 1u;
                            if (c.rel_addr != 0) mbar_arrive_cluster(c.rel_addr + STAGE_BAR * 8 + (ga.buf[0][4][0] & 0u));
                        } else {
                            ga.fetch(c, 1);
                        }
                    }
                    if (st == 3 && layer == 0) {
                        char* op = slab(c, EX_O + role);
#pragma unroll
                        for (int u = 0; u < 5; u++) stv(op + u * 512, 0u, 0u, 0u, 0u);
                        if (w == 3) {
                            char* hq = prm.scr + (uint32_t)(G_HALO + (role * 2 + wg) * 3072 + c.lane16());
#pragma unroll
                            for (int u = 0; u < 12; u++) stv(hq + (u / 6) * (256 * 3072) + (u % 6) * 512, etag ^ 1u, 0u, 0u, 0u);
                        }
                    }
                };
                publish_x(c, X, EX_X + role, 1u, false);
                ln_head<GQKV, 4, 0>(q, ga, c, item0, X, xv, stoff, rsA, rsB, ax, clear_boxes, role, (TLSEL == 1 + layer * 4) ? 50 : 0, PROBE == 1 + 4 * layer);
                float qm[32], kv[64];
                wait_full(c, item0 + 5);
                wg_wait<0>();
                reg_fence(q.m);
                rename<32, 0>(qm, q.m);
                rename<64, 32>(kv, q.m);
#pragma unroll
                for (int st = 5; st < 8; st++) {
                    const uint32_t base = item16(c, item0 + st);
                    if (st == 7) order_wait<2>(c);
                    wg_fence();
#pragma unroll
                    for (int u = 0; u < 5; u++) {
                        wgmma_n128_acc(kv, ga.at(st)[u], mkdesc(base, u * 2048, 10240, 1024, 1));
                        wgmma_n48_acc(q.r, ga.at(st)[u], mkdesc(base, 20480 + u * 512, 2560, 256, 3));
                    }
                    if (st == 7) {
                        wgmma_n128_acc(kv, ax, mkdesc(c.sb16, OFF_XQM + 1024, 1024, 0, 1));
                        wgmma_n48_acc(q.r, ax, mkdesc(c.sb16, OFF_XQR, 256, 0, 3));
                    }
                    wg_commit();
                    if (st == 7) order_post<2>(c);
                    if (st > 5) wg_wait<1>();
                    release(c, item0 + st - 1);
                    wait_full(c, item0 + st + 1);
                    if (st == 5) {
                        ga.check(c, 6);
                        ga.fetch(c, 7);
                        sched_fence(c);
                    }
                    if (st == 6) {
                        if (layer == 0) mbar_wait0(sb + BAR_CS, c.budget);
                        ga.check(c, 7);
                    }
                }
                float rk1[2], rk2[2];
                {
                    const int t8 = (c.lane() & 3) * 8;
#pragma unroll
                    for (int e = 0; e < 2; e++) {
                        rk2[e] = __shfl_sync(0xffffffffu, rsB, t8 + 4 * e);
                        rk1[e] = __shfl_sync(0xffffffffu, rsA, t8 + 4 * e);
                    }
                }
                auto q_steps = [&](int n0, int n1) {
                    wg_fence();
#pragma unroll
                    for (int n = n0; n < n1; n++) {
                        if (n < 15) wgmma_n64_acc(qm, ga.at(5 + n / 5)[n % 5], mkdesc(item16(c, item0 + 8), n * 2048, 1024, 1024, 1));
                        else wgmma_n64_acc(qm, ax, mkdesc(c.sb16, OFF_XQM, 1024, 0, 1));
                    }
                    wg_commit();
                };
                q_steps(0, 7);
                wg_wait<1>();
                reg_fence(kv);
                reg_fence(q.r);
                release(c, item0 + 7);
                TLB(2 + layer * 16);
                uint32_t T[3][10][2];
                auto pack_tiles = [&](int pc, int h, bool main, bool rem, bool odd) {
#pragma unroll
                    for (int j = 0; j < 10; j++) {
                        const bool isrem = odd ? j < 2 : j >= 8;
                        const int e = isrem ? pc * 8 + 4 * (j & 1) + 2 * h : 4 * ((odd ? j + 6 : j) & 7) + 2 * h;
                        if (isrem) { if (rem) T[pc][j][h] = pack2(q.r[e], q.r[e + 1]); }
                        else if (main) T[pc][j][h] = pc == 0 ? pack2(qm[e], qm[e + 1]) : pack2(kv[(pc - 1) * 32 + e], kv[(pc - 1) * 32 + e + 1]);
                    }
                };
                if (r & 1) { pack_tiles(1, 1, true, true, true); pack_tiles(2, 1, true, true, true); }
                else { pack_tiles(1, 1, true, true, false); pack_tiles(2, 1, true, true, false); }
                auto hreg = [&](int n) -> uint32_t& { return n < 8 ? T[1][n + (n + 2) / 4][1] : n < 10 ? T[1][5 * n - 38][1] : T[2][n - 10][1]; };
                char* hg = prm.scr + (uint32_t)(G_HALO + ((layer * 128 + role) * 2 + wg) * 3072 + c.lane16());
                if (w == 3) {
#pragma unroll
                    for (int u = 0; u < 5; u++) {
                        hreg(4 * u) = tagged(hreg(4 * u), etag);
                        stv(hg + u * 512, hreg(4 * u), hreg(4 * u + 1), hreg(4 * u + 2), hreg(4 * u + 3));
                    }
                    stv(hg + 2560, tagged(__float_as_uint(rk2[0]), etag), __float_as_uint(rk2[1]), 0u, 0u);
                }
                if (r & 1) { pack_tiles(1, 0, true, true, true); pack_tiles(2, 0, true, true, true); }
                else { pack_tiles(1, 0, true, true, false); pack_tiles(2, 0, true, true, false); }
                unpark_x(X, c.park());
                q_steps(7, 16);
                if (w < 3) {
#pragma unroll
                    for (int u = 0; u < 5; u++)
                        asm volatile("stmatrix.sync.aligned.m8n8.x4.shared.b16 [%0], {%1,%2,%3,%4};" :: "r"(c.park() + u * 512),
                                     "r"(hreg(4 * u)), "r"(hreg(4 * u + 1)), "r"(hreg(4 * u + 2)), "r"(hreg(4 * u + 3)) : "memory");
                    if (c.lane() < 4) asm volatile("st.shared.v2.f32 [%0], {%1,%2};" :: "r"(sb + OFF_RK + warp * 32 + c.lane() * 8), "f"(rk2[0]), "f"(rk2[1]) : "memory");
                }
                asm volatile("bar.sync %0, 128;" :: "r"(1 + wg) : "memory");
                uint32_t H[6][4];
                auto hK = [&](int j) { return j == 2 ? H[2][0] : j == 7 ? H[2][1] : H[(j - (j + 2) / 5) >> 2][(j - (j + 2) / 5) & 3]; };
                auto hV = [&](int j) { return H[(j + 10) >> 2][(j + 10) & 3]; };
                auto hoff = [&]() { return (uint32_t)(G_HALO + ((layer * 128 + role - 8) * 2 + wg) * 3072 + c.lane16()); };
                if (w > 0) {
                    const uint32_t hs = c.park() - 2560;
#pragma unroll
                    for (int u = 0; u < 5; u++) {
                        if (u < 2) asm volatile("ldmatrix.sync.aligned.m8n8.x4.shared.b16 {%0,%1,%2,%3}, [%4];"
                                                : "=r"(H[u][0]), "=r"(H[u][1]), "=r"(H[u][2]), "=r"(H[u][3]) : "r"(hs + u * 512) : "memory");
                        if (u > 2) asm volatile("ldmatrix.sync.aligned.m8n8.x4.trans.shared.b16 {%0,%1,%2,%3}, [%4];"
                                                : "=r"(H[u][0]), "=r"(H[u][1]), "=r"(H[u][2]), "=r"(H[u][3]) : "r"(hs + u * 512) : "memory");
                    }
                    asm volatile("ldmatrix.sync.aligned.m8n8.x2.shared.b16 {%0,%1}, [%2];" : "=r"(H[2][0]), "=r"(H[2][1]) : "r"(hs + 1024) : "memory");
                    asm volatile("ldmatrix.sync.aligned.m8n8.x2.trans.shared.b16 {%0,%1}, [%2];" : "=r"(H[2][2]), "=r"(H[2][3]) : "r"(hs + 1280) : "memory");
                    asm volatile("ld.shared.v2.u32 {%0,%1}, [%2];" : "=r"(H[5][0]), "=r"(H[5][1]) : "r"(sb + OFF_RK + warp * 32 - 32 + (c.lane() & 3) * 8) : "memory");
                } else if (blk > 0) {
                    ld_vecs(H, prm.scr + hoff());
                } else {
#pragma unroll
                    for (int u = 0; u < 6; u++) { H[u][0] = 0u; H[u][1] = 0u; H[u][2] = 0u; H[u][3] = 0u; }
                }
                uint32_t Vt1[10], Vt2[10];
#pragma unroll
                for (int j = 0; j < 10; j++) { Vt1[j] = movm(T[2][j][0]); Vt2[j] = movm(T[2][j][1]); }
                if (MOVM_SHADOW) sched_fence(c);
                wg_wait<0>();
                reg_fence(qm);
                release(c, item0 + 8);
                if (r & 1) { pack_tiles(0, 0, true, true, true); pack_tiles(0, 1, true, true, true); }
                else { pack_tiles(0, 0, true, true, false); pack_tiles(0, 1, true, true, false); }
                TLB(3 + layer * 16);
                const int g = c.lane() >> 2, t = c.lane() & 3;
                const bool sel0 = 2 * t > g, sel1 = 2 * t + 1 > g;
                const float cs = 0.22360679774997896f * 1.4426950408889634f;
                const float kB0 = sel0 ? rk1[0] : rk2[0], kB1 = sel1 ? rk1[1] : rk2[1];
                const float fB0 = rsB * cs * kB0, fB1 = rsB * cs * kB1;
                float lA0[4], lA1[4], lB0[4], lB1[4];
                uint32_t qs[4][2];
#pragma unroll
                for (int h = 0; h < 4; h++) {
                    const int f0 = 5 * (h >> 1) + 3 * (h & 1), f1 = f0 + 1, s = 5 * (h >> 1) + 2;
                    const bool keep = (h & 1) ? (t >= 2) : (t < 2);
                    qs[h][0] = keep ? T[0][s][0] : 0u; qs[h][1] = keep ? T[0][s][1] : 0u;
                    float s1[4], s2[4];
                    mma_k8_init(s1, qs[h][0], qs[h][1], T[1][s][0]);
                    mma_k8_init(s2, qs[h][0], qs[h][1], T[1][s][1]);
                    mma_k16_acc(s1, T[0][f0][0], T[0][f0][1], T[0][f1][0], T[0][f1][1], T[1][f0][0], T[1][f1][0]);
                    mma_k16_acc(s2, T[0][f0][0], T[0][f0][1], T[0][f1][0], T[0][f1][1], T[1][f0][1], T[1][f1][1]);
                    lA0[h] = s1[0]; lA1[h] = s1[1];
                    lB0[h] = (sel0 ? s1[2] : s2[2]) * fB0;
                    lB1[h] = (sel1 ? s1[3] : s2[3]) * fB1;
                }
                wait_full(c, item0 + IT_WO);
                if (w == 0 && blk > 0) {
                    check_vecs(c, H, etag, hoff);
#pragma unroll
                    for (int n = 10; n < 20; n++) H[n >> 2][n & 3] = movm(H[n >> 2][n & 3]);
                }
                const bool first = (blk == 0) && (w == 0);
                const float kA0 = sel0 ? __uint_as_float(H[5][0]) : rk1[0], kA1 = sel1 ? __uint_as_float(H[5][1]) : rk1[1];
                const float fA0 = rsA * cs * kA0, fA1 = rsA * cs * kA1;
                const float bA0 = (first && sel0) ? -INFINITY : 0.f, bA1 = (first && sel1) ? -INFINITY : 0.f;
                const uint32_t M = (sel0 ? 0x0000ffffu : 0u) | (sel1 ? 0xffff0000u : 0u);
#pragma unroll
                for (int h = 0; h < 4; h++) {
                    const int f0 = 5 * (h >> 1) + 3 * (h & 1), f1 = f0 + 1, s = 5 * (h >> 1) + 2;
                    float s0[4];
                    mma_k8_init(s0, qs[h][0], qs[h][1], hK(s));
                    mma_k16_acc(s0, T[0][f0][0], T[0][f0][1], T[0][f1][0], T[0][f1][1], hK(f0), hK(f1));
                    lA0[h] = fmaf(sel0 ? s0[0] : lA0[h], fA0, bA0);
                    lA1[h] = fmaf(sel1 ? s0[1] : lA1[h], fA1, bA1);
                }
                uint32_t pA[4], pB[4];
#pragma unroll
                for (int h = 0; h < 4; h++) {
                    float mA = fmaxf(lA0[h], lA1[h]), mB = fmaxf(lB0[h], lB1[h]);
                    mA = fmaxf(mA, __shfl_xor_sync(0xffffffffu, mA, 1));
                    mB = fmaxf(mB, __shfl_xor_sync(0xffffffffu, mB, 1));
                    mA = fmaxf(mA, __shfl_xor_sync(0xffffffffu, mA, 2));
                    mB = fmaxf(mB, __shfl_xor_sync(0xffffffffu, mB, 2));
                    const float eA0 = ex2(lA0[h] - mA), eA1 = ex2(lA1[h] - mA), eB0 = ex2(lB0[h] - mB), eB1 = ex2(lB1[h] - mB);
                    float sA = eA0 + eA1, sB = eB0 + eB1;
                    sA += __shfl_xor_sync(0xffffffffu, sA, 1);
                    sB += __shfl_xor_sync(0xffffffffu, sB, 1);
                    sA += __shfl_xor_sync(0xffffffffu, sA, 2);
                    sB += __shfl_xor_sync(0xffffffffu, sB, 2);
                    const float iA = rcp(sA), iB = rcp(sB);
                    pA[h] = pack2(eA0 * kA0 * iA, eA1 * kA1 * iA);
                    pB[h] = pack2(eB0 * kB0 * iB, eB1 * kB1 * iB);
                }
                uint32_t Op[10][2];
#pragma unroll
                for (int h = 0; h < 4; h++) {
                    const int f0 = 5 * (h >> 1) + 3 * (h & 1), s = 5 * (h >> 1) + 2;
                    const uint32_t ap = pA[h] & M, a0 = pA[h] & ~M, a1 = pB[h] & M, a3 = pB[h] & ~M;
#pragma unroll
                    for (int i = 0; i < 3; i++) {
                        const int j = i < 2 ? f0 + i : s;
                        float o[4];
                        mma_k8_init(o, ap, 0u, hV(j));
                        mma_k16_acc(o, a0, a1, 0u, a3, Vt1[j], Vt2[j]);
                        const uint32_t o0 = pack2(o[0], o[1]), o1 = pack2(o[2], o[3]);
                        if (i < 2 || (h & 1) == 0) { Op[j][0] = o0; Op[j][1] = o1; }
                        else { Op[j][0] = t >= 2 ? o0 : Op[j][0]; Op[j][1] = t >= 2 ? o1 : Op[j][1]; }
                    }
                }
                PR(PROBE == 2, 0);
                char* op = slab(c, EX_O + role);
#pragma unroll
                for (int u = 0; u < 5; u++) {
                    O[u][0] = tagged(Op[2 * u][0], 1u); O[u][1] = Op[2 * u][1]; O[u][2] = Op[2 * u + 1][0]; O[u][3] = Op[2 * u + 1][1];
                    stv(op + u * 512, O[u][0], O[u][1], O[u][2], O[u][3]);
                }
            }
            TLB(4 + layer * 16);
            {
                PHASE_IDS
                GWO o;
                unpack_x(o.m, X);
                Gather<7> ga;
                ga.slab0 = EX_O + blk * 8; ga.tag = 1u;
                const int itw = item0 + IT_WO;
#pragma unroll
                for (int st = 0; st < 8; st++) {
                    if (st > 0 && (st & 1) == 0) wait_full(c, itw + st / 2); else sched_fence(c);
                    if (st == 1) order_wait<3>(c);
                    if (st == 6) order_wait<4>(c);
                    wg_fence();
                    if (st == 0) o.step<false>(O, item16(c, itw), 0, 0);
                    else o.step<false>(ga.at(st > 0 ? st : 1), item16(c, itw + st / 2), st & 1, 0);
                    wg_commit();
                    if (st == 1) order_post<3>(c);
                    if (st == 7) order_post<4>(c);
                    if (st == 0) {
                        sched_fence(c);
#pragma unroll
                        for (int i = 1; i <= WO_B1; i++) ga.fetch(c, i);
                    }
                    if (st > 0 && (st & 1) == 0) { wg_wait<1>(); release(c, itw + st / 2 - 1); }
                    if (st == 0 || st == WO_B1 || st == WO_B2) {
                        const int e0 = st == 0 ? WO_B1 : st == WO_B1 ? WO_B2 : 7, e1 = st == 0 ? WO_B2 : 7;
#pragma unroll
                        for (int i = st + 1; i <= e0; i++) ga.check(c, i);
#pragma unroll
                        for (int i = e0 + 1; i <= e1; i++) ga.fetch(c, i);
                    }
                    if (TLSEL == 2 + layer * 4) TL(50 + st);
                }
                wait_full(c, item0 + IT_W1);
                wg_wait<0>();
                reg_fence(o.m);
                release(c, item0 + IT_W1 - 1);
                TLB(5 + layer * 16);
                pack_x(X, o.m);
                if (DBG_STAGE == 1 + 2 * layer) store_out(c, X, prm.out + (size_t)(128 * blk + 32 * w + wg) * DM);
                publish_x(c, X, EX_X + role, 0u);

#pragma unroll
                for (int i = 0; i < 40; i++) xv[i] = o.m[i];
            }
            TLB(6 + layer * 16);
            {
                PHASE_IDS
                const int it1 = item0 + IT_W1, it0 = item0 + IT_W2;
                GW1 f;
                Gather<3> ga;
                ga.slab0 = EX_X + blk * 8; ga.tag = 0u;
                auto clear_h = [&](int st) {
                    if (st == -1) ga.fetch(c, 1);
                    if (CLEAR_H == 3 && st == 2 && layer == 0) {
                        char* hq = prm.scr + (uint32_t)(G_H + role * HSLAB + warp * 4608 + launder(c.wl));
                        stv(hq + 7 * 512, 0u, 0u, 0u, 0u);
                        stv(hq + 13 * 512, 0u, 0u, 0u, 0u);
                    }
                    if (CLEAR_H == 1 && st >= 2 && st <= 4 && layer == 0) {
                        char* hq = prm.scr + (uint32_t)(G_H + role * HSLAB + warp * 4608 + launder(c.wl));
#pragma unroll
                        for (int u = 5 * (st - 2); u < 5 * (st - 1) && u < 14; u++) stv(hq + u * 512, 0u, 0u, 0u, 0u);
                    }
                };
                uint32_t ax[4];
                ln_head<GW1, 5, 5>(f, ga, c, it1, X, xv, stoff, rsA, rsB, ax, clear_h, role, (TLSEL == 3 + layer * 4) ? 50 : 0, PROBE == 3);
                float fa[48], fb[64];
                if (layer == 0) mbar_wait0(sb + BAR_CS + 8, c.budget);
                wait_full(c, it1 + 6);
                wg_wait<0>();
                reg_fence(f.m);
                rename<64, 0>(fb, f.m);
                rename<48, 64>(fa, f.m);
#pragma unroll
                for (int st = 6; st < 8; st++) {
                    const uint32_t base = item16(c, it1 + 6);
                    if (st == 6) order_wait<7>(c);
                    wg_fence();
#pragma unroll
                    for (int u = 0; u < 5; u++)
                        wgmma_n96_acc(fa, ga.at(st)[u], mkdesc(base, (st - 6) * 15360 + u * 1024, 5120, 512, 2));
                    if (st == 6) {
                        order_post<7>(c);
                        release(c, it1 + 5);
                        wait_full(c, it1 + 7);
                        ga.check(c, 7);
                    }
                }
                wgmma_n96_acc(fa, ax, mkdesc(c.sb16, OFF_XW1 + 2048, 512, 0, 2));
                wg_commit();
                auto b_steps = [&](int n0, int n1) {
                    wg_fence();
#pragma unroll
                    for (int n = n0; n < n1; n++) {
                        if (n < 10) wgmma_n128_acc(fb, ga.at(6 + n / 5)[n % 5], mkdesc(item16(c, it1 + 7), (n / 5) * 20480 + (n % 5) * 1024, 5120, 512, 2));
                        else wgmma_n128_acc(fb, ax, mkdesc(c.sb16, OFF_XW1, 512, 0, 2));
                    }
                    wg_commit();
                };
                b_steps(0, 7);
                wait_full(c, it0);
                wg_wait<1>();
                reg_fence(fa);
                release(c, it1 + 6);
                TLB(7 + layer * 16);
                auto hoff = [&](int st) {
                    return (uint32_t)(G_H + launder(blk * 8 + hsrc_at(st, r)) * HSLAB + warp * 4608 + (hpartB(st) ? 0 : 4096) + launder(c.wl));
                };
                auto hptr = [&](int st) { return prm.scr + hoff(st); };
                uint32_t Ha[6][4], Hb[8][4];
                {
                    char* dst = hptr(0);
#pragma unroll
                    for (int k = 0; k < 6; k++) {
#pragma unroll
                        for (int i = 0; i < 4; i++) Ha[k][i] = pack2_relu(fa[8 * k + 2 * i], fa[8 * k + 2 * i + 1]);
                        Ha[k][0] = tagged(Ha[k][0], ltag);
                        stv(dst + k * 512, Ha[k][0], Ha[k][1], Ha[k][2], Ha[k][3]);
                    }
                }
                sched_fence(c);
                b_steps(7, 11);
                wg_wait<0>();
                reg_fence(fb);
#pragma unroll
                for (int k = 0; k < 8; k++) {
#pragma unroll
                    for (int i = 0; i < 4; i++) Hb[k][i] = pack2_relu(fb[8 * k + 2 * i], fb[8 * k + 2 * i + 1]);
                }
                sched_fence(c);
                float acc[80];
                uint32_t bufa[3][6][4], buf[3][8][4];
                auto step_a = [&](int st, const uint32_t (&a)[6][4]) {
                    const uint32_t base = item16(c, it0 + st);
                    wg_fence();
#pragma unroll
                    for (int k = 0; k < 6; k++) {
                        const uint64_t d = mkdesc(base, k * 1024, 6144, 512, 2);
                        if (st == 0 && k == 0) wgmma_n160_init(acc, a[k], d); else wgmma_n160_acc(acc, a[k], d);
                    }
                    wg_commit();
                };
                auto step_b = [&](int st, const uint32_t (&a)[8][4]) {
                    const uint32_t base = item16(c, it0 + st);
                    wg_fence();
#pragma unroll
                    for (int k = 0; k < 8; k++) wgmma_n160_acc(acc, a[k], mkdesc(base, k * 1024, 8192, 512, 2));
                    wg_commit();
                };
                auto hprobe = [&](int vec) {
                    if (CLEAR_H == 3 && layer == 0) {
                        const char* pp = prm.scr + (uint32_t)(G_H + (blk * 8 + (r & 1) + 2 * (c.lane() & 3)) * HSLAB + warp * 7168 + vec * 512 + 496);
                        uint32_t v;
                        do {
                            asm volatile("ld.relaxed.gpu.global.u32 %0, [%1];" : "=r"(v) : "l"(pp) : "memory");
                        } while (__any_sync(0xffffffffu, !(v & 1u)) && --c.budget >= 0);
                    }
                };
                auto hfetch = [&](int st) { if (st < 5) ld_vecs(bufa[st - 2], hptr(st)); else ld_vecs(buf[st - 5], hptr(st)); };
                auto hcheck = [&](int st) {
                    if (st < 5) check_vecs(c, bufa[st < 5 ? st - 2 : 0], ltag, [&]() { return hoff(st); });
                    else check_vecs(c, buf[st < 5 ? 0 : st - 5], ltag, [&]() { return hoff(st); });
                };
                step_a(0, Ha);
                release(c, it1 + 7);
                wait_full(c, it0 + 1);
                hprobe(13);
                hfetch(2);
                {
                    char* dst = hptr(1);
#pragma unroll
                    for (int k = 0; k < 8; k++) {
                        Hb[k][0] = tagged(Hb[k][0], ltag);
                        stv(dst + k * 512, Hb[k][0], Hb[k][1], Hb[k][2], Hb[k][3]);
                    }
                }
                sched_fence(c);
                step_b(1, Hb);
                wg_wait<1>();
                release(c, it0);
                hcheck(2);
                hfetch(3);
                if (layer == 1) TLB(41);
#pragma unroll
                for (int st = 2; st < 6; st++) {
                    wait_full(c, it0 + st);
                    if (st == 2) order_wait<8>(c);
                    if (st < 5) step_a(st, bufa[st < 5 ? st - 2 : 0]); else step_b(st, buf[0]);
                    if (st == 2) order_post<8>(c);
                    wg_wait<1>();
                    release(c, it0 + st - 1);
                    hcheck(st + 1);
                    if (st == 3) hprobe(7);
                    hfetch(st + 2);
                    if (layer == 1) TLB(40 + st);
                }
                wait_full(c, it0 + 6);
                wg_wait<0>();
                reg_fence(acc);
                float own[32], par[48];
                rename<48, 32>(par, acc);
                rename<32, 0>(own, acc);
#pragma unroll
                for (int st = 6; st < 8; st++) {
                    if (st == 6) order_wait<9>(c);
                    if (st == 7) { order_post<9>(c); release(c, it0 + 5); wait_full(c, it0 + st); hcheck(7); order_wait<10>(c); }
                    const uint32_t base = item16(c, it0 + st);
                    wg_fence();
#pragma unroll
                    for (int k = 0; k < 8; k++) wgmma_n96_acc(par, buf[st - 5][k], mkdesc(base, k * 1024, 8192, 512, 2));
                    wg_commit();
                }
                order_post<10>(c);
                wait_full(c, it0 + 8);
                {
                    const uint32_t base = item16(c, it0 + 8);
                    wg_fence();
#pragma unroll
                    for (int k = 0; k < 8; k++) wgmma_n64_acc(own, buf[1][k], mkdesc(base, k * 1024, 8192, 512, 2));
                    wg_commit();
                }
                wg_wait<1>();
                reg_fence(par);
                release(c, it0 + 6);
                release(c, it0 + 7);
                float rem[8];
                {
                    char* dst = slab(c, EX_O + role);
                    const bool odd = r & 1;
#pragma unroll
                    for (int u = 0; u < 5; u++) {
                        uint32_t v[4];
#pragma unroll
                        for (int i = 0; i < 4; i++) {
                            const int e = 8 * u + 2 * i;
                            if (u < 4) v[i] = pack2(par[e], par[e + 1]);
                            else v[i] = pack2(odd ? par[e] : par[e + 8], odd ? par[e + 1] : par[e + 9]);
                        }
                        stv(dst + u * 512, tagged(v[0], 0u), v[1], v[2], v[3]);
                    }
#pragma unroll
                    for (int i = 0; i < 8; i++) rem[i] = odd ? par[40 + i] : par[32 + i];
                }
                sched_fence(c);
                {
                    const uint32_t base = item16(c, it0 + 8);
                    wg_fence();
#pragma unroll
                    for (int k = 0; k < 8; k++) wgmma_n64_acc(own, buf[2][k], mkdesc(base, 16384 + k * 1024, 8192, 512, 2));
                    wg_commit();
                }
                if (layer == 1) TLB(47);
                sched_fence(c);
                uint32_t P[5][4];
                ld_vecs(P, slab(c, EX_O + (role ^ 1)));
                unpark_x(X, c.park());
                if (layer == 0) wait_full(c, NITEMS_L);
                check_vecs(c, P, 0u, [&]() { return slab_off(c, EX_O + (role ^ 1)); });
                wg_wait<0>();
                reg_fence(own);
                release(c, it0 + 8);
                TLB(8 + layer * 16);
#pragma unroll
                for (int u = 0; u < 5; u++)
#pragma unroll
                    for (int i = 0; i < 4; i++) {
                        const float rs = (i & 1) ? rsB : rsA;
                        const int e = 8 * u + 2 * i;
                        xv[e] = fmaf(rs, (u < 4 ? own[e & 31] : rem[e & 7]) + bf_lo(P[u][i]), bf_lo(X[u][i]));
                        xv[e + 1] = fmaf(rs, (u < 4 ? own[(e + 1) & 31] : rem[(e + 1) & 7]) + bf_hi(P[u][i]), bf_hi(X[u][i]));
                    }
                pack_x(X, xv);
                if (DBG_STAGE == 2 + 2 * layer) store_out(c, X, prm.out + (size_t)(128 * blk + 32 * w + wg) * DM);
                            if (layer == 1) break;
                park_x(c.park(), X);
            }
            TLB(9 + layer * 16);
        }
        TL(25);
        TLDUMP(64);
        if (warp == 0) reinterpret_cast<unsigned*>(prm.scr + G_EPOCH + role * 128)[c.lane()] = etag;
    } else {
        int budget = SPIN_BUDGET;
        asm volatile("setmaxnreg.dec.sync.aligned.u32 %0;" :: "n"(REG_HELP));
        auto publish_cs = [&](float (&a)[8], char* cs, int lane, uint32_t tag) {
#pragma unroll
            for (int i = 0; i < 8; i++) a[i] += __shfl_down_sync(0xffffffffu, a[i], 10) + __shfl_down_sync(0xffffffffu, a[i], 20);
            if (lane < 10) {
                char* dst = cs + blk * 320 + lane * 32;
                stv(dst, tagged(__float_as_uint(a[0]), tag), __float_as_uint(a[1]), __float_as_uint(a[2]), __float_as_uint(a[3]));
                stv(dst + 16, tagged(__float_as_uint(a[4]), tag), __float_as_uint(a[5]), __float_as_uint(a[6]), __float_as_uint(a[7]));
            }
        };
        uint32_t etag = 0;
        if (warp > 8) {
#pragma unroll 1
            for (int i = threadIdx.x - 288; i < XTRA_BYTES / 16; i += 96)
                asm volatile("st.shared.v4.u32 [%0], {%1,%1,%1,%1};" :: "r"(sb + OFF_XQM + i * 16), "r"(0) : "memory");
            asm volatile("bar.sync 5, 96;" ::: "memory");
            etag = (etag0 & 1u) ^ 1u;
            char* cs = prm.scr + (uint32_t)(G_CS + (r * 6 + warp - 9) * 5120);
            if (lane < 10) {
#pragma unroll
                for (int i = 0; i < 4; i++) stv(cs + blk * 320 + lane * 32 + (i >> 1) * 3 * 5120 + (i & 1) * 16, etag ^ 1u, 0u, 0u, 0u);
            }
            if (CS_LOAD0 >= 0) mbar_wait0(sb + BAR_FULL + (CS_LOAD0 < 0 ? 0 : CS_LOAD0) * 8, budget);
            TLH(11);
            const int rp = lane < 30 ? (lane * 13) >> 7 : 2, ch = lane < 30 ? lane - 10 * rp : 0;
            const char* src = reinterpret_cast<const char*>(prm.wqkv + (40 * blk + rp) * DQKV + 640 * (warp - 9) + 80 * r + 8 * ch);
            float a[8] = {0.f, 0.f, 0.f, 0.f, 0.f, 0.f, 0.f, 0.f};
#pragma unroll 1
            for (int h = 0; h < 2; h++) {
                uint32_t w[7][4];
                const bool last = h == 0 || rp == 0;
#pragma unroll
                for (int i = 0; i < 6; i++) ldv(w[i], src + i * 6 * DQKV);
                ldv(w[6], src + (last ? 36 * DQKV : 0));
#pragma unroll
                for (int i = 0; i < 7; i++)
#pragma unroll
                    for (int e = 0; e < 4; e++) {
                        const uint32_t v = (i < 6 || last) ? w[i][e] : 0u;
                        a[2 * e] += bf_lo(v); a[2 * e + 1] += bf_hi(v);
                    }
                src += 42 * DQKV;
            }
            publish_cs(a, cs, lane, etag);
            TLH(12);
        }
        if (warp == 8) {
            TL(5);
            if (elect_one()) {
#pragma unroll 1
                for (int i = NOMC; i < NITEMS; i++) {
                    const uint32_t dep = (prm.item[i] >> 16) & 0xffu;
                    if (dep != 0xffu) mbar_wait0(sb + BAR_EMPTY + dep * 8, budget);
                    if (i >= INFLIGHT) mbar_wait0(sb + BAR_FULL + (i - INFLIGHT) * 8, budget);
                    produce(i);
                    if (i == 2) TL(3);
                    if ((BPF & 2) && i == BPF_A) {
                        l2_prefetch(prm.wo + blockIdx.x * (DM * DM / 128), DM * DM / 64);
                        l2_prefetch(prm.w1 + blockIdx.x * (DM * DFF / 128), DM * DFF / 64);
                    }
                    if ((BPF & 4) && i == BPF_B) l2_prefetch(prm.w2 + blockIdx.x * (DM * DFF / 128), DM * DFF / 64);
                    if (i == 3) {
                        asm volatile("prefetch.tensormap [%0];" :: "l"(&tmWO) : "memory");
                        asm volatile("prefetch.tensormap [%0];" :: "l"(&tmW1a) : "memory");
                        asm volatile("prefetch.tensormap [%0];" :: "l"(&tmW1b) : "memory");
                        asm volatile("prefetch.tensormap [%0];" :: "l"(&tmW2) : "memory");
                        asm volatile("prefetch.tensormap [%0];" :: "l"(&tmW2a) : "memory");
                    }
                }
            }
            __syncwarp();
            TLDUMP(16);
        } else {
#pragma unroll 1
            for (int mat = 0; mat < 2; mat++) {
                const int lane = launder(threadIdx.x & 31), j = launder(warp) - 9;
                char* cs = prm.scr + (uint32_t)(G_CS + ((r * 2 + mat) * 3 + j) * 5120);
                float a[8] = {0.f, 0.f, 0.f, 0.f, 0.f, 0.f, 0.f, 0.f};
                if (mat) {
                    const int rp = (lane * 13) >> 7, ch = lane - 10 * rp;
                    const int col = 224 * r + 80 * j + 8 * ch;
                    const int nrow = (rp < 3 && (10 * j + ch) < 28 && col < DFF) ? (rp == 0 ? 14 : 13) : 0;
                    const char* src = reinterpret_cast<const char*>(prm.w1 + (40 * blk + rp) * DFF + col);
#pragma unroll 1
                    for (int i = 0; i < ((BPF & 2) ? 0 : nrow); i++) asm volatile("prefetch.global.L2 [%0];" :: "l"(src + i * 6 * DFF));
                    __syncwarp();
                    mbar_wait0(sb + BAR_EMPTY + CS_LOAD1 * 8, budget);
#pragma unroll 1
                    for (int i0 = 0; i0 < 14; i0 += CS_BATCH) {
                        uint32_t w[CS_BATCH][4];
#pragma unroll
                        for (int i = 0; i < CS_BATCH; i++)
                            asm volatile("{.reg .pred p; setp.lt.s32 p, %5, %6; mov.b32 %0, 0; mov.b32 %1, 0; mov.b32 %2, 0; mov.b32 %3, 0;\n"
                                         "@p ld.global.cg.v4.u32 {%0,%1,%2,%3}, [%4];}"
                                         : "=r"(w[i][0]), "=r"(w[i][1]), "=r"(w[i][2]), "=r"(w[i][3]) : "l"(src + i * 6 * DFF), "r"(i0 + i), "r"(nrow));
#pragma unroll
                        for (int i = 0; i < CS_BATCH; i++)
#pragma unroll
                            for (int e = 0; e < 4; e++) { a[2 * e] += bf_lo(w[i][e]); a[2 * e + 1] += bf_hi(w[i][e]); }
                        src += CS_BATCH * 6 * DFF;
                    }
                    publish_cs(a, cs, lane, etag);
                }

                cs += (lane < 20 ? lane : 0) * 16;
                a[0] = 0.f; a[1] = 0.f; a[2] = 0.f; a[3] = 0.f;
#pragma unroll 1
                for (int b0 = 0; b0 < 16;) {
                    uint32_t v[CS_GB][4];
#pragma unroll
                    for (int i = 0; i < CS_GB; i++) ldv(v[i], cs + i * 320);
                    if (bad_vecs(v, etag) && --budget >= 0) continue;
#pragma unroll
                    for (int i = 0; i < CS_GB; i++)
#pragma unroll
                        for (int e = 0; e < 4; e++) a[e] -= __uint_as_float(v[i][e]);
                    b0 += CS_GB;
                    cs += CS_GB * 320;
                }
                if (mat == 0) TLH(14);
                const uint32_t h0 = pack2(a[0], a[1]), h1 = pack2(a[2], a[3]);
                const uint32_t l0 = pack2(a[0] - bf_lo(h0), a[1] - bf_hi(h0)), l1 = pack2(a[2] - bf_lo(h1), a[3] - bf_hi(h1));
                const int cc = 4 * launder(lane), cm = cc - 16 * (r & 1), cw = 80 * j + cc;
                const bool mainp = cm >= 0 && cm < 64;
                const uint32_t sh = mat ? 6 : mainp ? 7 : 5;
                const uint32_t ad = sb + (mat ? OFF_XW1 + (cw >> 5) * 512 + (cw & 31) * 2 : mainp ? OFF_XQM + j * 1024 + cm * 2 : OFF_XQR + j * 256 + (cc & 15) * 2);
                if (cc < 80 && (!mat || cw < 224)) {
#pragma unroll
                    for (int row = 0; row < 4; row++) {
                        const uint32_t o = row << sh;
                        asm volatile("st.shared.v2.u32 [%0], {%1,%2};" :: "r"((ad + o) ^ ((o >> 7) << 4)), "r"(row < 2 ? h0 : l0), "r"(row < 2 ? h1 : l1) : "memory");
                    }
                }
                asm volatile("fence.proxy.async.shared::cta;" ::: "memory");
                if (CLEAR_H == 2 && mat) __threadfence();
                __syncwarp();
                if (lane == 0) mbar_arrive(sb + BAR_CS + mat * 8);
                if (CLEAR_H == 2 && !mat) {
                    char* hq = prm.scr + (uint32_t)(G_H + role * HSLAB + lane * 16);
#pragma unroll 1
                    for (int i = j; i < HSLAB / 512; i += 3) { stv(hq + i * 512, 0u, 0u, 0u, 0u); __nanosleep(CLR_NS); }
                }
            }
        }
    }
}

typedef CUresult (*EncodeFn)(CUtensorMap*, CUtensorMapDataType, cuuint32_t, void*, const cuuint64_t*, const cuuint64_t*,
                             const cuuint32_t*, const cuuint32_t*, CUtensorMapInterleave, CUtensorMapSwizzle,
                             CUtensorMapL2promotion, CUtensorMapFloatOOBfill);

void encode(EncodeFn fn, CUtensorMap* tm, const void* ptr, int rank, const cuuint64_t* dims, const cuuint64_t* strides,
            const cuuint32_t* box, CUtensorMapSwizzle sw) {
    const cuuint32_t es[3] = {1, 1, 1};
    fn(tm, CU_TENSOR_MAP_DATA_TYPE_BFLOAT16, rank, const_cast<void*>(ptr), dims, strides, box, es, CU_TENSOR_MAP_INTERLEAVE_NONE, sw,
       CU_TENSOR_MAP_L2_PROMOTION_L2_128B, CU_TENSOR_MAP_FLOAT_OOB_FILL_NONE);
}

__global__ void occupancy_probe_kernel() {}

struct RoleMap { int v[64]; };
RoleMap make_role_map() {
    RoleMap rm;
    for (int i = 0; i < 64; i++) rm.v[i] = ((i & 7) << 3) | (i >> 3);
    cudaFuncSetAttribute(occupancy_probe_kernel, cudaFuncAttributeMaxDynamicSharedMemorySize, SMEM_BYTES);
    cudaFuncSetAttribute(occupancy_probe_kernel, cudaFuncAttributeNonPortableClusterSizeAllowed, 1);
    int N[17] = {0};
    for (int cs = 2; cs <= 16; cs++) {
        cudaLaunchConfig_t cfg = {};
        cfg.gridDim = dim3(cs * 8); cfg.blockDim = dim3(384); cfg.dynamicSmemBytes = SMEM_BYTES;
        cudaLaunchAttribute at[1];
        at[0].id = cudaLaunchAttributeClusterDimension;
        at[0].val.clusterDim.x = cs; at[0].val.clusterDim.y = 1; at[0].val.clusterDim.z = 1;
        cfg.attrs = at; cfg.numAttrs = 1;
        if (cudaOccupancyMaxActiveClusters(&N[cs], occupancy_probe_kernel, &cfg) != cudaSuccess) { cudaGetLastError(); return rm; }
    }
    int ge[10] = {0};
    for (int k = 5; k <= 8; k++) ge[k] = N[2 * k];
    ge[9] = N[9] - ge[5];
    ge[4] = N[8] - ge[8];
    ge[3] = N[6] - ge[6] - ge[9];
    ge[2] = N[4] - ge[4] - ge[6] - ge[8];
    ge[1] = ge[2];
    int total = 0;
    for (int k = 1; k <= 9; k++) { if (ge[k] < 0 || ge[k] > 16 || (k > 1 && ge[k] > ge[k - 1])) return rm; total += ge[k]; }
    const int singles = N[2] - total;
    if (singles < 0 || N[2] < 64) return rm;
    int col[64], cnt[17] = {0}, n = 0;
    for (; n < singles && n < 64; n++) col[n] = 16;
    for (int k = 1; k <= 9; k++)
        for (int j = 0; j < ge[k] && n < 64; j++) col[n++] = (cnt[j]++ < 8) ? j : 16;
    if (n != 64) return rm;
    int pos = 0;
    for (int j = 0; j <= 16; j++)
        for (int i = 0; i < 64; i++)
            if (col[i] == j) { const int q = pos & 7; rm.v[i] = (pos & ~7) | (2 * (q & 3) + (q >> 2)); pos++; }
    return rm;
}

}

extern "C" void kernel_launch(void* const* d_in, const int* in_sizes, int n_in, void* d_out, int out_size) {
    const __nv_bfloat16* x = (const __nv_bfloat16*)d_in[0];
    const __nv_bfloat16* wqkv = (const __nv_bfloat16*)d_in[1];
    const __nv_bfloat16* wo = (const __nv_bfloat16*)d_in[2];
    const __nv_bfloat16* w1 = (const __nv_bfloat16*)d_in[4];
    const __nv_bfloat16* w2 = (const __nv_bfloat16*)d_in[5];

    void* fnp = nullptr;
    cudaDriverEntryPointQueryResult qr;
    cudaGetDriverEntryPoint("cuTensorMapEncodeTiled", &fnp, cudaEnableDefault, &qr);
    EncodeFn fn = (EncodeFn)fnp;
    CUtensorMap tmQM, tmQR, tmWO, tmW1a, tmW1b, tmW2, tmW2a;
    {
        const cuuint64_t dims[3] = {640, 640, 3}, strides[2] = {DQKV * 2, 640 * 2};
        const cuuint64_t dims2[2] = {DQKV, 640};
        const cuuint32_t bm[2] = {64, 80}, br[3] = {16, 80, 3};
        encode(fn, &tmQM, wqkv, 2, dims2, strides, bm, CU_TENSOR_MAP_SWIZZLE_128B);
        encode(fn, &tmQR, wqkv, 3, dims, strides, br, CU_TENSOR_MAP_SWIZZLE_32B);
    }
    {
        const cuuint64_t dims[2] = {640, 640}, strides[1] = {640 * 2};
        const cuuint32_t box[2] = {32, 80};
        encode(fn, &tmWO, wo, 2, dims, strides, box, CU_TENSOR_MAP_SWIZZLE_64B);
    }
    {
        const cuuint64_t dims[3] = {32, 640, 54}, strides[2] = {DFF * 2, 64};
        const cuuint32_t boxa[3] = {32, 80, 3}, boxb[3] = {32, 80, 4};
        encode(fn, &tmW1a, w1, 3, dims, strides, boxa, CU_TENSOR_MAP_SWIZZLE_64B);
        encode(fn, &tmW1b, w1, 3, dims, strides, boxb, CU_TENSOR_MAP_SWIZZLE_64B);
    }
    {
        const cuuint64_t dims[2] = {640, DFF}, strides[1] = {640 * 2};
        const cuuint32_t box[2] = {32, 128}, boxa[2] = {32, 96};
        encode(fn, &tmW2, w2, 2, dims, strides, box, CU_TENSOR_MAP_SWIZZLE_64B);
        encode(fn, &tmW2a, w2, 2, dims, strides, boxa, CU_TENSOR_MAP_SWIZZLE_64B);
    }
    cudaFuncSetAttribute(fused_layers_kernel, cudaFuncAttributeMaxDynamicSharedMemorySize, SMEM_LAUNCH);
    const RoleMap rm = make_role_map();
    Params prm;
    void* scr = nullptr;
    cudaGetSymbolAddress(&scr, g_scratch);
    prm.scr = (char*)scr;
    prm.minus1 = -1; prm.pad = 0;
    prm.xin = x; prm.wqkv = wqkv; prm.w1 = w1; prm.wo = wo; prm.w2 = w2; prm.out = (__nv_bfloat16*)d_out;
    constexpr ItemTab tab = make_tab();
    for (int i = 0; i < 64; i++) prm.role[i] = (uint8_t)rm.v[i];
    for (int i = 0; i < NITEMS; i++) prm.item[i] = (uint32_t)(tab.off[i] >> 4) | (uint32_t)(tab.dep[i] & 0xff) << 16 | (uint32_t)tab.rel[i] << 24;
    fused_layers_kernel<<<128, 384, SMEM_LAUNCH>>>(prm, tmQM, tmQR, tmWO, tmW1a, tmW1b, tmW2, tmW2a);
}
```

```cpp
#include <cuda_runtime.h>
#include <cuda_bf16.h>
#include <cuda.h>
#include <stdint.h>

#define DBG_STAGE 4
#define TLSEL 0
#define WO_B1 2
#define WO_B2 5
#define ORDER 0x1b
#define CS_GATE 0
#define WO_EARLY 0
#define LATE 8
#define TLW 0
#define OORDER 0
#define PAUSE 0
#define QUADS 0
#define XPROBE 0
#define CLR_HALO 1
#define CLR_O 0x44332
#define HB0 3
#define HB1 3
#define INFL_UNTIL 5
#define L2PROMO CU_TENSOR_MAP_L2_PROMOTION_NONE
#define PFW 0
#define XL 0
#define XPF 0
#define PUBF 3
#define FETCH_FENCE 1

namespace {

constexpr int DM = 640, DQKV = 1920, DFF = 1728;
constexpr float LN_EPS = 1e-5f;
constexpr int SPIN_BUDGET = 1 << 20;
constexpr int REG_HELP = 56, REG_CONS = 224;

constexpr int NSLOT = 5, NITEMS_L = 30, NITEMS = 60;
constexpr int IT_WO = 9, IT_W1 = 13, IT_W2 = 21;
__host__ __device__ constexpr int slot_off(int k) { return k % 5 < 4 ? (k % 5) * 40960 : 3 * 40960 + 38912; }
constexpr int RING_BYTES = 3 * 40960 + 2 * 38912;
constexpr int STAGE_OFF = slot_off(3);

constexpr int OFF_XQM = RING_BYTES;
constexpr int OFF_XW1 = OFF_XQM + 3072;
constexpr int OFF_XQR = OFF_XW1 + 3584;
constexpr int XTRA_BYTES = 7424;
constexpr int OFF_PARK = OFF_XQM + XTRA_BYTES;
constexpr int OFF_RK = OFF_PARK + 8 * 2560;
constexpr int BAR_FULL = OFF_RK + 256, BAR_EMPTY = BAR_FULL + 40, BAR_STAGE = BAR_EMPTY + 40, BAR_CS = BAR_STAGE + 8, BAR_ORD = BAR_CS + 16;
constexpr int NORD = 5;
constexpr int SMEM_BYTES = BAR_ORD + NORD * 8;
static_assert(SMEM_BYTES <= 232448 - 512, "smem");

constexpr int V_X = 0, V_O = 5, V_HB = 10, V_HA = 18, V_ST = 24, V_HALO = 25;
constexpr int WBOX = 5 * 512, RBOX = 8 * WBOX, PLANE = 8 * RBOX, BBOX = 9 * PLANE;
__host__ __device__ constexpr int voff(int v) { return v / 5 * PLANE + v % 5 * 512; }
constexpr uint32_t G_CS = 16 * BBOX;
constexpr uint32_t G_EPOCH = G_CS + 8 * 2 * 3 * 5120;
constexpr uint32_t G_BYTES = G_EPOCH + 128 * 128;
__device__ __align__(1024) uint4 g_scratch[G_BYTES / 16];

struct Params {
    char* scr;
    const __nv_bfloat16 *xin, *wqkv, *w1;
    __nv_bfloat16* out;
    uint8_t role[64];
};

#define TL(slot) do {} while (0)
#define TLH(slot) do {} while (0)
#define TLDUMP(n) do {} while (0)
#define TLINIT
constexpr int SMEM_LAUNCH = SMEM_BYTES;

template <int N> struct IntC { static constexpr int value = N; };
__device__ __forceinline__ uint32_t smem_u32(const void* p) { return (uint32_t)__cvta_generic_to_shared(p); }
__device__ __forceinline__ int launder(int v) { asm volatile("" : "+r"(v)); return v; }
__device__ __forceinline__ bool elect_one() {
    uint32_t p;
    asm volatile("{.reg .pred q; elect.sync _|q, 0xffffffff; selp.u32 %0, 1, 0, q;}" : "=r"(p));
    return p;
}
__device__ __forceinline__ void mbar_init(uint32_t b, int c) { asm volatile("mbarrier.init.shared::cta.b64 [%0], %1;" :: "r"(b), "r"(c) : "memory"); }
__device__ __forceinline__ void mbar_expect(uint32_t b, int bytes) { asm volatile("mbarrier.arrive.expect_tx.shared::cta.b64 _, [%0], %1;" :: "r"(b), "r"(bytes) : "memory"); }
__device__ __forceinline__ void mbar_arrive(uint32_t b) { asm volatile("mbarrier.arrive.shared::cta.b64 _, [%0];" :: "r"(b) : "memory"); }
__device__ __forceinline__ void mbar_arrive_cluster(uint32_t b) { asm volatile("mbarrier.arrive.shared::cluster.b64 _, [%0];" :: "r"(b) : "memory"); }
__device__ __forceinline__ void mbar_wait(uint32_t b, uint32_t parity, int& budget) {
    uint32_t ok;
#pragma unroll 1
    do {
        asm volatile("{.reg .pred p; mbarrier.try_wait.parity.shared::cta.b64 p, [%1], %2; selp.u32 %0, 1, 0, p;}" : "=r"(ok) : "r"(b), "r"(parity) : "memory");
    } while (!ok && --budget >= 0);
}
__device__ __forceinline__ void ldv(uint32_t (&v)[4], const void* p) {
    asm volatile("{.reg .b128 t; ld.relaxed.gpu.global.b128 t, [%4]; mov.b128 {%0,%1,%2,%3}, t;}"
                 : "=r"(v[0]), "=r"(v[1]), "=r"(v[2]), "=r"(v[3]) : "l"(p) : "memory");
}
__device__ __forceinline__ void stv(void* p, uint32_t a, uint32_t b, uint32_t c, uint32_t d) {
    asm volatile("{.reg .b128 t; mov.b128 t, {%0,%1,%2,%3}; st.relaxed.gpu.global.b128 [%4], t;}"
                 :: "r"(a), "r"(b), "r"(c), "r"(d), "l"(p) : "memory");
}
__device__ __forceinline__ uint32_t tagged(uint32_t w, uint32_t tag) { return (w & ~1u) | tag; }
__device__ __forceinline__ uint32_t pack2(float lo, float hi) {
    uint32_t r; asm("cvt.rn.bf16x2.f32 %0, %1, %2;" : "=r"(r) : "f"(hi), "f"(lo)); return r;
}
__device__ __forceinline__ uint32_t pack2_relu(float lo, float hi) {
    uint32_t r; asm("cvt.rn.relu.bf16x2.f32 %0, %1, %2;" : "=r"(r) : "f"(hi), "f"(lo)); return r;
}
__device__ __forceinline__ float bf_lo(uint32_t w) { return __uint_as_float(w << 16); }
__device__ __forceinline__ float bf_hi(uint32_t w) { return __uint_as_float(w & 0xffff0000u); }
__device__ __forceinline__ uint32_t movm(uint32_t a) {
    uint32_t r; asm volatile("movmatrix.sync.aligned.m8n8.trans.b16 %0, %1;" : "=r"(r) : "r"(a)); return r;
}
__device__ __forceinline__ void ldsm4(uint32_t (&v)[4], uint32_t a) {
    asm volatile("ldmatrix.sync.aligned.m8n8.x4.shared.b16 {%0,%1,%2,%3}, [%4];" : "=r"(v[0]), "=r"(v[1]), "=r"(v[2]), "=r"(v[3]) : "r"(a) : "memory");
}
__device__ __forceinline__ void ldsm4t(uint32_t (&v)[4], uint32_t a) {
    asm volatile("ldmatrix.sync.aligned.m8n8.x4.trans.shared.b16 {%0,%1,%2,%3}, [%4];" : "=r"(v[0]), "=r"(v[1]), "=r"(v[2]), "=r"(v[3]) : "r"(a) : "memory");
}
__device__ __forceinline__ void stsm4(uint32_t a, uint32_t v0, uint32_t v1, uint32_t v2, uint32_t v3) {
    asm volatile("stmatrix.sync.aligned.m8n8.x4.shared.b16 [%0], {%1,%2,%3,%4};" :: "r"(a), "r"(v0), "r"(v1), "r"(v2), "r"(v3) : "memory");
}
__device__ __forceinline__ float ex2(float x) { float r; asm("ex2.approx.ftz.f32 %0, %1;" : "=f"(r) : "f"(x)); return r; }
__device__ __forceinline__ float rcp(float x) { float r; asm("rcp.approx.ftz.f32 %0, %1;" : "=f"(r) : "f"(x)); return r; }
__device__ __forceinline__ float rsq(float x) { float r; asm("rsqrt.approx.ftz.f32 %0, %1;" : "=f"(r) : "f"(x)); return r; }
__device__ __forceinline__ void mma_k8_init(float (&d)[4], uint32_t a0, uint32_t a1, uint32_t b0) {
    asm volatile("mma.sync.aligned.m16n8k8.row.col.f32.bf16.bf16.f32 {%0,%1,%2,%3}, {%4,%5}, {%6}, {%7,%7,%7,%7};"
                 : "=f"(d[0]), "=f"(d[1]), "=f"(d[2]), "=f"(d[3]) : "r"(a0), "r"(a1), "r"(b0), "f"(0.f));
}
__device__ __forceinline__ void mma_k16_acc(float (&d)[4], uint32_t a0, uint32_t a1, uint32_t a2, uint32_t a3, uint32_t b0, uint32_t b1) {
    asm volatile("mma.sync.aligned.m16n8k16.row.col.f32.bf16.bf16.f32 {%0,%1,%2,%3}, {%4,%5,%6,%7}, {%8,%9}, {%0,%1,%2,%3};"
                 : "+f"(d[0]), "+f"(d[1]), "+f"(d[2]), "+f"(d[3]) : "r"(a0), "r"(a1), "r"(a2), "r"(a3), "r"(b0), "r"(b1));
}
__device__ __forceinline__ void wg_fence() { asm volatile("wgmma.fence.sync.aligned;" ::: "memory"); }
__device__ __forceinline__ void wg_commit() { asm volatile("wgmma.commit_group.sync.aligned;" ::: "memory"); }
template <int N> __device__ __forceinline__ void wg_wait() { asm volatile("wgmma.wait_group.sync.aligned %0;" :: "n"(N) : "memory"); }
template <int N> __device__ __forceinline__ void reg_fence(float (&d)[N]) {
#pragma unroll
    for (int i = 0; i < N; i++) asm volatile("" : "+f"(d[i]) :: "memory");
}
template <int N, int OFF, int TOT> __device__ __forceinline__ void rename(float (&d)[N], const float (&s)[TOT]) {
#pragma unroll
    for (int i = 0; i < N; i++) asm volatile("mov.f32 %0, %1;" : "=f"(d[i]) : "f"(s[OFF + i]));
}
__device__ __forceinline__ uint64_t mkdesc(uint32_t a16, uint32_t off, uint32_t lbo, uint32_t sbo, int sw) {
    const uint32_t lo = a16 + ((off >> 4) + ((lbo >> 4) << 16));
    const uint32_t hi = (sbo >> 4) | ((uint32_t)sw << 30);
    return ((uint64_t)hi << 32) | lo;
}
__device__ __forceinline__ void tma2d_mc(uint32_t dst, const CUtensorMap* tm, int c0, int c1, uint32_t bar) {
    asm volatile("cp.async.bulk.tensor.2d.shared::cluster.global.mbarrier::complete_tx::bytes.multicast::cluster [%0], [%1, {%3, %4}], [%2], %5;"
                 :: "r"(dst), "l"(tm), "r"(bar), "r"(c0), "r"(c1), "h"((uint16_t)3) : "memory");
}
__device__ __forceinline__ void tma3d_mc(uint32_t dst, const CUtensorMap* tm, int c0, int c1, int c2, uint32_t bar) {
    asm volatile("cp.async.bulk.tensor.3d.shared::cluster.global.mbarrier::complete_tx::bytes.multicast::cluster [%0], [%1, {%3, %4, %5}], [%2], %6;"
                 :: "r"(dst), "l"(tm), "r"(bar), "r"(c0), "r"(c1), "r"(c2), "h"((uint16_t)3) : "memory");
}
__device__ __forceinline__ void prefetch_map(const CUtensorMap* tm) { asm volatile("prefetch.tensormap [%0];" :: "l"(tm) : "memory"); }

__device__ __forceinline__ void wgmma_n192_acc(float (&d)[96], const uint32_t (&a)[4], uint64_t db) {
    asm volatile("{.reg .pred p; setp.eq.b32 p, 0, 0;\n"
        "wgmma.mma_async.sync.aligned.m64n192k16.f32.bf16.bf16 {"
        "%0, %1, %2, %3, %4, %5, %6, %7, %8, %9, %10, %11, %12, %13, %14, %15, %16, %17, %18, %19, %20, %21, %22, %23, "
        "%24, %25, %26, %27, %28, %29, %30, %31, %32, %33, %34, %35, %36, %37, %38, %39, %40, %41, %42, %43, %44, %45, %46, %47, "
        "%48, %49, %50, %51, %52, %53, %54, %55, %56, %57, %58, %59, %60, %61, %62, %63, %64, %65, %66, %67, %68, %69, %70, %71, "
        "%72, %73, %74, %75, %76, %77, %78, %79, %80, %81, %82, %83, %84, %85, %86, %87, %88, %89, %90, %91, %92, %93, %94, %95"
        "}, {%96, %97, %98, %99}, %100, p, 1, 1, 1;}\n"
        : "+f"(d[0]), "+f"(d[1]), "+f"(d[2]), "+f"(d[3]), "+f"(d[4]), "+f"(d[5]), "+f"(d[6]), "+f"(d[7]), "+f"(d[8]), "+f"(d[9]), "+f"(d[10]), "+f"(d[11]),
          "+f"(d[12]), "+f"(d[13]), "+f"(d[14]), "+f"(d[15]), "+f"(d[16]), "+f"(d[17]), "+f"(d[18]), "+f"(d[19]), "+f"(d[20]), "+f"(d[21]), "+f"(d[22]), "+f"(d[23]),
          "+f"(d[24]), "+f"(d[25]), "+f"(d[26]), "+f"(d[27]), "+f"(d[28]), "+f"(d[29]), "+f"(d[30]), "+f"(d[31]), "+f"(d[32]), "+f"(d[33]), "+f"(d[34]), "+f"(d[35]),
          "+f"(d[36]), "+f"(d[37]), "+f"(d[38]), "+f"(d[39]), "+f"(d[40]), "+f"(d[41]), "+f"(d[42]), "+f"(d[43]), "+f"(d[44]), "+f"(d[45]), "+f"(d[46]), "+f"(d[47]),
          "+f"(d[48]), "+f"(d[49]), "+f"(d[50]), "+f"(d[51]), "+f"(d[52]), "+f"(d[53]), "+f"(d[54]), "+f"(d[55]), "+f"(d[56]), "+f"(d[57]), "+f"(d[58]), "+f"(d[59]),
          "+f"(d[60]), "+f"(d[61]), "+f"(d[62]), "+f"(d[63]), "+f"(d[64]), "+f"(d[65]), "+f"(d[66]), "+f"(d[67]), "+f"(d[68]), "+f"(d[69]), "+f"(d[70]), "+f"(d[71]),
          "+f"(d[72]), "+f"(d[73]), "+f"(d[74]), "+f"(d[75]), "+f"(d[76]), "+f"(d[77]), "+f"(d[78]), "+f"(d[79]), "+f"(d[80]), "+f"(d[81]), "+f"(d[82]), "+f"(d[83]),
          "+f"(d[84]), "+f"(d[85]), "+f"(d[86]), "+f"(d[87]), "+f"(d[88]), "+f"(d[89]), "+f"(d[90]), "+f"(d[91]), "+f"(d[92]), "+f"(d[93]), "+f"(d[94]), "+f"(d[95])
        : "r"(a[0]), "r"(a[1]), "r"(a[2]), "r"(a[3]), "l"(db));
}
__device__ __forceinline__ void wgmma_n192_init(float (&d)[96], const uint32_t (&a)[4], uint64_t db) {
    asm volatile("{.reg .pred p; setp.ne.b32 p, 0, 0;\n"
        "wgmma.mma_async.sync.aligned.m64n192k16.f32.bf16.bf16 {"
        "%0, %1, %2, %3, %4, %5, %6, %7, %8, %9, %10, %11, %12, %13, %14, %15, %16, %17, %18, %19, %20, %21, %22, %23, "
        "%24, %25, %26, %27, %28, %29, %30, %31, %32, %33, %34, %35, %36, %37, %38, %39, %40, %41, %42, %43, %44, %45, %46, %47, "
        "%48, %49, %50, %51, %52, %53, %54, %55, %56, %57, %58, %59, %60, %61, %62, %63, %64, %65, %66, %67, %68, %69, %70, %71, "
        "%72, %73, %74, %75, %76, %77, %78, %79, %80, %81, %82, %83, %84, %85, %86, %87, %88, %89, %90, %91, %92, %93, %94, %95"
        "}, {%96, %97, %98, %99}, %100, p, 1, 1, 1;}\n"
        : "=f"(d[0]), "=f"(d[1]), "=f"(d[2]), "=f"(d[3]), "=f"(d[4]), "=f"(d[5]), "=f"(d[6]), "=f"(d[7]), "=f"(d[8]), "=f"(d[9]), "=f"(d[10]), "=f"(d[11]),
          "=f"(d[12]), "=f"(d[13]), "=f"(d[14]), "=f"(d[15]), "=f"(d[16]), "=f"(d[17]), "=f"(d[18]), "=f"(d[19]), "=f"(d[20]), "=f"(d[21]), "=f"(d[22]), "=f"(d[23]),
          "=f"(d[24]), "=f"(d[25]), "=f"(d[26]), "=f"(d[27]), "=f"(d[28]), "=f"(d[29]), "=f"(d[30]), "=f"(d[31]), "=f"(d[32]), "=f"(d[33]), "=f"(d[34]), "=f"(d[35]),
          "=f"(d[36]), "=f"(d[37]), "=f"(d[38]), "=f"(d[39]), "=f"(d[40]), "=f"(d[41]), "=f"(d[42]), "=f"(d[43]), "=f"(d[44]), "=f"(d[45]), "=f"(d[46]), "=f"(d[47]),
          "=f"(d[48]), "=f"(d[49]), "=f"(d[50]), "=f"(d[51]), "=f"(d[52]), "=f"(d[53]), "=f"(d[54]), "=f"(d[55]), "=f"(d[56]), "=f"(d[57]), "=f"(d[58]), "=f"(d[59]),
          "=f"(d[60]), "=f"(d[61]), "=f"(d[62]), "=f"(d[63]), "=f"(d[64]), "=f"(d[65]), "=f"(d[66]), "=f"(d[67]), "=f"(d[68]), "=f"(d[69]), "=f"(d[70]), "=f"(d[71]),
          "=f"(d[72]), "=f"(d[73]), "=f"(d[74]), "=f"(d[75]), "=f"(d[76]), "=f"(d[77]), "=f"(d[78]), "=f"(d[79]), "=f"(d[80]), "=f"(d[81]), "=f"(d[82]), "=f"(d[83]),
          "=f"(d[84]), "=f"(d[85]), "=f"(d[86]), "=f"(d[87]), "=f"(d[88]), "=f"(d[89]), "=f"(d[90]), "=f"(d[91]), "=f"(d[92]), "=f"(d[93]), "=f"(d[94]), "=f"(d[95])
        : "r"(a[0]), "r"(a[1]), "r"(a[2]), "r"(a[3]), "l"(db));
}
__device__ __forceinline__ void wgmma_n48_acc(float (&d)[24], const uint32_t (&a)[4], uint64_t db) {
    asm volatile("{.reg .pred p; setp.eq.b32 p, 0, 0;\n"
        "wgmma.mma_async.sync.aligned.m64n48k16.f32.bf16.bf16 {"
        "%0, %1, %2, %3, %4, %5, %6, %7, %8, %9, %10, %11, %12, %13, %14, %15, %16, %17, %18, %19, %20, %21, %22, %23"
        "}, {%24, %25, %26, %27}, %28, p, 1, 1, 1;}\n"
        : "+f"(d[0]), "+f"(d[1]), "+f"(d[2]), "+f"(d[3]), "+f"(d[4]), "+f"(d[5]), "+f"(d[6]), "+f"(d[7]), "+f"(d[8]), "+f"(d[9]), "+f"(d[10]), "+f"(d[11]),
          "+f"(d[12]), "+f"(d[13]), "+f"(d[14]), "+f"(d[15]), "+f"(d[16]), "+f"(d[17]), "+f"(d[18]), "+f"(d[19]), "+f"(d[20]), "+f"(d[21]), "+f"(d[22]), "+f"(d[23])
        : "r"(a[0]), "r"(a[1]), "r"(a[2]), "r"(a[3]), "l"(db));
}
__device__ __forceinline__ void wgmma_n48_init(float (&d)[24], const uint32_t (&a)[4], uint64_t db) {
    asm volatile("{.reg .pred p; setp.ne.b32 p, 0, 0;\n"
        "wgmma.mma_async.sync.aligned.m64n48k16.f32.bf16.bf16 {"
        "%0, %1, %2, %3, %4, %5, %6, %7, %8, %9, %10, %11, %12, %13, %14, %15, %16, %17, %18, %19, %20, %21, %22, %23"
        "}, {%24, %25, %26, %27}, %28, p, 1, 1, 1;}\n"
        : "=f"(d[0]), "=f"(d[1]), "=f"(d[2]), "=f"(d[3]), "=f"(d[4]), "=f"(d[5]), "=f"(d[6]), "=f"(d[7]), "=f"(d[8]), "=f"(d[9]), "=f"(d[10]), "=f"(d[11]),
          "=f"(d[12]), "=f"(d[13]), "=f"(d[14]), "=f"(d[15]), "=f"(d[16]), "=f"(d[17]), "=f"(d[18]), "=f"(d[19]), "=f"(d[20]), "=f"(d[21]), "=f"(d[22]), "=f"(d[23])
        : "r"(a[0]), "r"(a[1]), "r"(a[2]), "r"(a[3]), "l"(db));
}
__device__ __forceinline__ void wgmma_n224_acc(float (&d)[112], const uint32_t (&a)[4], uint64_t db) {
    asm volatile("{.reg .pred p; setp.eq.b32 p, 0, 0;\n"
        "wgmma.mma_async.sync.aligned.m64n224k16.f32.bf16.bf16 {"
        "%0, %1, %2, %3, %4, %5, %6, %7, %8, %9, %10, %11, %12, %13, %14, %15, %16, %17, %18, %19, %20, %21, %22, %23, "
        "%24, %25, %26, %27, %28, %29, %30, %31, %32, %33, %34, %35, %36, %37, %38, %39, %40, %41, %42, %43, %44, %45, %46, %47, "
        "%48, %49, %50, %51, %52, %53, %54, %55, %56, %57, %58, %59, %60, %61, %62, %63, %64, %65, %66, %67, %68, %69, %70, %71, "
        "%72, %73, %74, %75, %76, %77, %78, %79, %80, %81, %82, %83, %84, %85, %86, %87, %88, %89, %90, %91, %92, %93, %94, %95, "
        "%96, %97, %98, %99, %100, %101, %102, %103, %104, %105, %106, %107, %108, %109, %110, %111"
        "}, {%112, %113, %114, %115}, %116, p, 1, 1, 1;}\n"
        : "+f"(d[0]), "+f"(d[1]), "+f"(d[2]), "+f"(d[3]), "+f"(d[4]), "+f"(d[5]), "+f"(d[6]), "+f"(d[7]), "+f"(d[8]), "+f"(d[9]), "+f"(d[10]), "+f"(d[11]),
          "+f"(d[12]), "+f"(d[13]), "+f"(d[14]), "+f"(d[15]), "+f"(d[16]), "+f"(d[17]), "+f"(d[18]), "+f"(d[19]), "+f"(d[20]), "+f"(d[21]), "+f"(d[22]), "+f"(d[23]),
          "+f"(d[24]), "+f"(d[25]), "+f"(d[26]), "+f"(d[27]), "+f"(d[28]), "+f"(d[29]), "+f"(d[30]), "+f"(d[31]), "+f"(d[32]), "+f"(d[33]), "+f"(d[34]), "+f"(d[35]),
          "+f"(d[36]), "+f"(d[37]), "+f"(d[38]), "+f"(d[39]), "+f"(d[40]), "+f"(d[41]), "+f"(d[42]), "+f"(d[43]), "+f"(d[44]), "+f"(d[45]), "+f"(d[46]), "+f"(d[47]),
          "+f"(d[48]), "+f"(d[49]), "+f"(d[50]), "+f"(d[51]), "+f"(d[52]), "+f"(d[53]), "+f"(d[54]), "+f"(d[55]), "+f"(d[56]), "+f"(d[57]), "+f"(d[58]), "+f"(d[59]),
          "+f"(d[60]), "+f"(d[61]), "+f"(d[62]), "+f"(d[63]), "+f"(d[64]), "+f"(d[65]), "+f"(d[66]), "+f"(d[67]), "+f"(d[68]), "+f"(d[69]), "+f"(d[70]), "+f"(d[71]),
          "+f"(d[72]), "+f"(d[73]), "+f"(d[74]), "+f"(d[75]), "+f"(d[76]), "+f"(d[77]), "+f"(d[78]), "+f"(d[79]), "+f"(d[80]), "+f"(d[81]), "+f"(d[82]), "+f"(d[83]),
          "+f"(d[84]), "+f"(d[85]), "+f"(d[86]), "+f"(d[87]), "+f"(d[88]), "+f"(d[89]), "+f"(d[90]), "+f"(d[91]), "+f"(d[92]), "+f"(d[93]), "+f"(d[94]), "+f"(d[95]),
          "+f"(d[96]), "+f"(d[97]), "+f"(d[98]), "+f"(d[99]), "+f"(d[100]), "+f"(d[101]), "+f"(d[102]), "+f"(d[103]), "+f"(d[104]), "+f"(d[105]), "+f"(d[106]), "+f"(d[107]),
          "+f"(d[108]), "+f"(d[109]), "+f"(d[110]), "+f"(d[111])
        : "r"(a[0]), "r"(a[1]), "r"(a[2]), "r"(a[3]), "l"(db));
}
__device__ __forceinline__ void wgmma_n224_init(float (&d)[112], const uint32_t (&a)[4], uint64_t db) {
    asm volatile("{.reg .pred p; setp.ne.b32 p, 0, 0;\n"
        "wgmma.mma_async.sync.aligned.m64n224k16.f32.bf16.bf16 {"
        "%0, %1, %2, %3, %4, %5, %6, %7, %8, %9, %10, %11, %12, %13, %14, %15, %16, %17, %18, %19, %20, %21, %22, %23, "
        "%24, %25, %26, %27, %28, %29, %30, %31, %32, %33, %34, %35, %36, %37, %38, %39, %40, %41, %42, %43, %44, %45, %46, %47, "
        "%48, %49, %50, %51, %52, %53, %54, %55, %56, %57, %58, %59, %60, %61, %62, %63, %64, %65, %66, %67, %68, %69, %70, %71, "
        "%72, %73, %74, %75, %76, %77, %78, %79, %80, %81, %82, %83, %84, %85, %86, %87, %88, %89, %90, %91, %92, %93, %94, %95, "
        "%96, %97, %98, %99, %100, %101, %102, %103, %104, %105, %106, %107, %108, %109, %110, %111"
        "}, {%112, %113, %114, %115}, %116, p, 1, 1, 1;}\n"
        : "=f"(d[0]), "=f"(d[1]), "=f"(d[2]), "=f"(d[3]), "=f"(d[4]), "=f"(d[5]), "=f"(d[6]), "=f"(d[7]), "=f"(d[8]), "=f"(d[9]), "=f"(d[10]), "=f"(d[11]),
          "=f"(d[12]), "=f"(d[13]), "=f"(d[14]), "=f"(d[15]), "=f"(d[16]), "=f"(d[17]), "=f"(d[18]), "=f"(d[19]), "=f"(d[20]), "=f"(d[21]), "=f"(d[22]), "=f"(d[23]),
          "=f"(d[24]), "=f"(d[25]), "=f"(d[26]), "=f"(d[27]), "=f"(d[28]), "=f"(d[29]), "=f"(d[30]), "=f"(d[31]), "=f"(d[32]), "=f"(d[33]), "=f"(d[34]), "=f"(d[35]),
          "=f"(d[36]), "=f"(d[37]), "=f"(d[38]), "=f"(d[39]), "=f"(d[40]), "=f"(d[41]), "=f"(d[42]), "=f"(d[43]), "=f"(d[44]), "=f"(d[45]), "=f"(d[46]), "=f"(d[47]),
          "=f"(d[48]), "=f"(d[49]), "=f"(d[50]), "=f"(d[51]), "=f"(d[52]), "=f"(d[53]), "=f"(d[54]), "=f"(d[55]), "=f"(d[56]), "=f"(d[57]), "=f"(d[58]), "=f"(d[59]),
          "=f"(d[60]), "=f"(d[61]), "=f"(d[62]), "=f"(d[63]), "=f"(d[64]), "=f"(d[65]), "=f"(d[66]), "=f"(d[67]), "=f"(d[68]), "=f"(d[69]), "=f"(d[70]), "=f"(d[71]),
          "=f"(d[72]), "=f"(d[73]), "=f"(d[74]), "=f"(d[75]), "=f"(d[76]), "=f"(d[77]), "=f"(d[78]), "=f"(d[79]), "=f"(d[80]), "=f"(d[81]), "=f"(d[82]), "=f"(d[83]),
          "=f"(d[84]), "=f"(d[85]), "=f"(d[86]), "=f"(d[87]), "=f"(d[88]), "=f"(d[89]), "=f"(d[90]), "=f"(d[91]), "=f"(d[92]), "=f"(d[93]), "=f"(d[94]), "=f"(d[95]),
          "=f"(d[96]), "=f"(d[97]), "=f"(d[98]), "=f"(d[99]), "=f"(d[100]), "=f"(d[101]), "=f"(d[102]), "=f"(d[103]), "=f"(d[104]), "=f"(d[105]), "=f"(d[106]), "=f"(d[107]),
          "=f"(d[108]), "=f"(d[109]), "=f"(d[110]), "=f"(d[111])
        : "r"(a[0]), "r"(a[1]), "r"(a[2]), "r"(a[3]), "l"(db));
}
__device__ __forceinline__ void wgmma_n80_acc(float (&d)[40], const uint32_t (&a)[4], uint64_t db) {
    asm volatile("{.reg .pred p; setp.eq.b32 p, 0, 0;\n"
        "wgmma.mma_async.sync.aligned.m64n80k16.f32.bf16.bf16 {"
        "%0, %1, %2, %3, %4, %5, %6, %7, %8, %9, %10, %11, %12, %13, %14, %15, %16, %17, %18, %19, %20, %21, %22, %23, "
        "%24, %25, %26, %27, %28, %29, %30, %31, %32, %33, %34, %35, %36, %37, %38, %39"
        "}, {%40, %41, %42, %43}, %44, p, 1, 1, 1;}\n"
        : "+f"(d[0]), "+f"(d[1]), "+f"(d[2]), "+f"(d[3]), "+f"(d[4]), "+f"(d[5]), "+f"(d[6]), "+f"(d[7]), "+f"(d[8]), "+f"(d[9]), "+f"(d[10]), "+f"(d[11]),
          "+f"(d[12]), "+f"(d[13]), "+f"(d[14]), "+f"(d[15]), "+f"(d[16]), "+f"(d[17]), "+f"(d[18]), "+f"(d[19]), "+f"(d[20]), "+f"(d[21]), "+f"(d[22]), "+f"(d[23]),
          "+f"(d[24]), "+f"(d[25]), "+f"(d[26]), "+f"(d[27]), "+f"(d[28]), "+f"(d[29]), "+f"(d[30]), "+f"(d[31]), "+f"(d[32]), "+f"(d[33]), "+f"(d[34]), "+f"(d[35]),
          "+f"(d[36]), "+f"(d[37]), "+f"(d[38]), "+f"(d[39])
        : "r"(a[0]), "r"(a[1]), "r"(a[2]), "r"(a[3]), "l"(db));
}
__device__ __forceinline__ void wgmma_n160_acc(float (&d)[80], const uint32_t (&a)[4], uint64_t db) {
    asm volatile("{.reg .pred p; setp.eq.b32 p, 0, 0;\n"
        "wgmma.mma_async.sync.aligned.m64n160k16.f32.bf16.bf16 {"
        "%0, %1, %2, %3, %4, %5, %6, %7, %8, %9, %10, %11, %12, %13, %14, %15, %16, %17, %18, %19, %20, %21, %22, %23, "
        "%24, %25, %26, %27, %28, %29, %30, %31, %32, %33, %34, %35, %36, %37, %38, %39, %40, %41, %42, %43, %44, %45, %46, %47, "
        "%48, %49, %50, %51, %52, %53, %54, %55, %56, %57, %58, %59, %60, %61, %62, %63, %64, %65, %66, %67, %68, %69, %70, %71, "
        "%72, %73, %74, %75, %76, %77, %78, %79"
        "}, {%80, %81, %82, %83}, %84, p, 1, 1, 1;}\n"
        : "+f"(d[0]), "+f"(d[1]), "+f"(d[2]), "+f"(d[3]), "+f"(d[4]), "+f"(d[5]), "+f"(d[6]), "+f"(d[7]), "+f"(d[8]), "+f"(d[9]), "+f"(d[10]), "+f"(d[11]),
          "+f"(d[12]), "+f"(d[13]), "+f"(d[14]), "+f"(d[15]), "+f"(d[16]), "+f"(d[17]), "+f"(d[18]), "+f"(d[19]), "+f"(d[20]), "+f"(d[21]), "+f"(d[22]), "+f"(d[23]),
          "+f"(d[24]), "+f"(d[25]), "+f"(d[26]), "+f"(d[27]), "+f"(d[28]), "+f"(d[29]), "+f"(d[30]), "+f"(d[31]), "+f"(d[32]), "+f"(d[33]), "+f"(d[34]), "+f"(d[35]),
          "+f"(d[36]), "+f"(d[37]), "+f"(d[38]), "+f"(d[39]), "+f"(d[40]), "+f"(d[41]), "+f"(d[42]), "+f"(d[43]), "+f"(d[44]), "+f"(d[45]), "+f"(d[46]), "+f"(d[47]),
          "+f"(d[48]), "+f"(d[49]), "+f"(d[50]), "+f"(d[51]), "+f"(d[52]), "+f"(d[53]), "+f"(d[54]), "+f"(d[55]), "+f"(d[56]), "+f"(d[57]), "+f"(d[58]), "+f"(d[59]),
          "+f"(d[60]), "+f"(d[61]), "+f"(d[62]), "+f"(d[63]), "+f"(d[64]), "+f"(d[65]), "+f"(d[66]), "+f"(d[67]), "+f"(d[68]), "+f"(d[69]), "+f"(d[70]), "+f"(d[71]),
          "+f"(d[72]), "+f"(d[73]), "+f"(d[74]), "+f"(d[75]), "+f"(d[76]), "+f"(d[77]), "+f"(d[78]), "+f"(d[79])
        : "r"(a[0]), "r"(a[1]), "r"(a[2]), "r"(a[3]), "l"(db));
}
__device__ __forceinline__ void wgmma_n160_init(float (&d)[80], const uint32_t (&a)[4], uint64_t db) {
    asm volatile("{.reg .pred p; setp.ne.b32 p, 0, 0;\n"
        "wgmma.mma_async.sync.aligned.m64n160k16.f32.bf16.bf16 {"
        "%0, %1, %2, %3, %4, %5, %6, %7, %8, %9, %10, %11, %12, %13, %14, %15, %16, %17, %18, %19, %20, %21, %22, %23, "
        "%24, %25, %26, %27, %28, %29, %30, %31, %32, %33, %34, %35, %36, %37, %38, %39, %40, %41, %42, %43, %44, %45, %46, %47, "
        "%48, %49, %50, %51, %52, %53, %54, %55, %56, %57, %58, %59, %60, %61, %62, %63, %64, %65, %66, %67, %68, %69, %70, %71, "
        "%72, %73, %74, %75, %76, %77, %78, %79"
        "}, {%80, %81, %82, %83}, %84, p, 1, 1, 1;}\n"
        : "=f"(d[0]), "=f"(d[1]), "=f"(d[2]), "=f"(d[3]), "=f"(d[4]), "=f"(d[5]), "=f"(d[6]), "=f"(d[7]), "=f"(d[8]), "=f"(d[9]), "=f"(d[10]), "=f"(d[11]),
          "=f"(d[12]), "=f"(d[13]), "=f"(d[14]), "=f"(d[15]), "=f"(d[16]), "=f"(d[17]), "=f"(d[18]), "=f"(d[19]), "=f"(d[20]), "=f"(d[21]), "=f"(d[22]), "=f"(d[23]),
          "=f"(d[24]), "=f"(d[25]), "=f"(d[26]), "=f"(d[27]), "=f"(d[28]), "=f"(d[29]), "=f"(d[30]), "=f"(d[31]), "=f"(d[32]), "=f"(d[33]), "=f"(d[34]), "=f"(d[35]),
          "=f"(d[36]), "=f"(d[37]), "=f"(d[38]), "=f"(d[39]), "=f"(d[40]), "=f"(d[41]), "=f"(d[42]), "=f"(d[43]), "=f"(d[44]), "=f"(d[45]), "=f"(d[46]), "=f"(d[47]),
          "=f"(d[48]), "=f"(d[49]), "=f"(d[50]), "=f"(d[51]), "=f"(d[52]), "=f"(d[53]), "=f"(d[54]), "=f"(d[55]), "=f"(d[56]), "=f"(d[57]), "=f"(d[58]), "=f"(d[59]),
          "=f"(d[60]), "=f"(d[61]), "=f"(d[62]), "=f"(d[63]), "=f"(d[64]), "=f"(d[65]), "=f"(d[66]), "=f"(d[67]), "=f"(d[68]), "=f"(d[69]), "=f"(d[70]), "=f"(d[71]),
          "=f"(d[72]), "=f"(d[73]), "=f"(d[74]), "=f"(d[75]), "=f"(d[76]), "=f"(d[77]), "=f"(d[78]), "=f"(d[79])
        : "r"(a[0]), "r"(a[1]), "r"(a[2]), "r"(a[3]), "l"(db));
}
__device__ __forceinline__ void wgmma_n128_acc(float (&d)[64], const uint32_t (&a)[4], uint64_t db) {
    asm volatile("{.reg .pred p; setp.eq.b32 p, 0, 0;\n"
        "wgmma.mma_async.sync.aligned.m64n128k16.f32.bf16.bf16 {"
        "%0, %1, %2, %3, %4, %5, %6, %7, %8, %9, %10, %11, %12, %13, %14, %15, %16, %17, %18, %19, %20, %21, %22, %23, "
        "%24, %25, %26, %27, %28, %29, %30, %31, %32, %33, %34, %35, %36, %37, %38, %39, %40, %41, %42, %43, %44, %45, %46, %47, "
        "%48, %49, %50, %51, %52, %53, %54, %55, %56, %57, %58, %59, %60, %61, %62, %63"
        "}, {%64, %65, %66, %67}, %68, p, 1, 1, 1;}\n"
        : "+f"(d[0]), "+f"(d[1]), "+f"(d[2]), "+f"(d[3]), "+f"(d[4]), "+f"(d[5]), "+f"(d[6]), "+f"(d[7]), "+f"(d[8]), "+f"(d[9]), "+f"(d[10]), "+f"(d[11]),
          "+f"(d[12]), "+f"(d[13]), "+f"(d[14]), "+f"(d[15]), "+f"(d[16]), "+f"(d[17]), "+f"(d[18]), "+f"(d[19]), "+f"(d[20]), "+f"(d[21]), "+f"(d[22]), "+f"(d[23]),
          "+f"(d[24]), "+f"(d[25]), "+f"(d[26]), "+f"(d[27]), "+f"(d[28]), "+f"(d[29]), "+f"(d[30]), "+f"(d[31]), "+f"(d[32]), "+f"(d[33]), "+f"(d[34]), "+f"(d[35]),
          "+f"(d[36]), "+f"(d[37]), "+f"(d[38]), "+f"(d[39]), "+f"(d[40]), "+f"(d[41]), "+f"(d[42]), "+f"(d[43]), "+f"(d[44]), "+f"(d[45]), "+f"(d[46]), "+f"(d[47]),
          "+f"(d[48]), "+f"(d[49]), "+f"(d[50]), "+f"(d[51]), "+f"(d[52]), "+f"(d[53]), "+f"(d[54]), "+f"(d[55]), "+f"(d[56]), "+f"(d[57]), "+f"(d[58]), "+f"(d[59]),
          "+f"(d[60]), "+f"(d[61]), "+f"(d[62]), "+f"(d[63])
        : "r"(a[0]), "r"(a[1]), "r"(a[2]), "r"(a[3]), "l"(db));
}
__device__ __forceinline__ void wgmma_n96_acc(float (&d)[48], const uint32_t (&a)[4], uint64_t db) {
    asm volatile("{.reg .pred p; setp.eq.b32 p, 0, 0;\n"
        "wgmma.mma_async.sync.aligned.m64n96k16.f32.bf16.bf16 {"
        "%0, %1, %2, %3, %4, %5, %6, %7, %8, %9, %10, %11, %12, %13, %14, %15, %16, %17, %18, %19, %20, %21, %22, %23, "
        "%24, %25, %26, %27, %28, %29, %30, %31, %32, %33, %34, %35, %36, %37, %38, %39, %40, %41, %42, %43, %44, %45, %46, %47"
        "}, {%48, %49, %50, %51}, %52, p, 1, 1, 1;}\n"
        : "+f"(d[0]), "+f"(d[1]), "+f"(d[2]), "+f"(d[3]), "+f"(d[4]), "+f"(d[5]), "+f"(d[6]), "+f"(d[7]), "+f"(d[8]), "+f"(d[9]), "+f"(d[10]), "+f"(d[11]),
          "+f"(d[12]), "+f"(d[13]), "+f"(d[14]), "+f"(d[15]), "+f"(d[16]), "+f"(d[17]), "+f"(d[18]), "+f"(d[19]), "+f"(d[20]), "+f"(d[21]), "+f"(d[22]), "+f"(d[23]),
          "+f"(d[24]), "+f"(d[25]), "+f"(d[26]), "+f"(d[27]), "+f"(d[28]), "+f"(d[29]), "+f"(d[30]), "+f"(d[31]), "+f"(d[32]), "+f"(d[33]), "+f"(d[34]), "+f"(d[35]),
          "+f"(d[36]), "+f"(d[37]), "+f"(d[38]), "+f"(d[39]), "+f"(d[40]), "+f"(d[41]), "+f"(d[42]), "+f"(d[43]), "+f"(d[44]), "+f"(d[45]), "+f"(d[46]), "+f"(d[47])
        : "r"(a[0]), "r"(a[1]), "r"(a[2]), "r"(a[3]), "l"(db));
}
__device__ __forceinline__ void wgmma_n64_acc(float (&d)[32], const uint32_t (&a)[4], uint64_t db) {
    asm volatile("{.reg .pred p; setp.eq.b32 p, 0, 0;\n"
        "wgmma.mma_async.sync.aligned.m64n64k16.f32.bf16.bf16 {"
        "%0, %1, %2, %3, %4, %5, %6, %7, %8, %9, %10, %11, %12, %13, %14, %15, %16, %17, %18, %19, %20, %21, %22, %23, "
        "%24, %25, %26, %27, %28, %29, %30, %31"
        "}, {%32, %33, %34, %35}, %36, p, 1, 1, 1;}\n"
        : "+f"(d[0]), "+f"(d[1]), "+f"(d[2]), "+f"(d[3]), "+f"(d[4]), "+f"(d[5]), "+f"(d[6]), "+f"(d[7]), "+f"(d[8]), "+f"(d[9]), "+f"(d[10]), "+f"(d[11]),
          "+f"(d[12]), "+f"(d[13]), "+f"(d[14]), "+f"(d[15]), "+f"(d[16]), "+f"(d[17]), "+f"(d[18]), "+f"(d[19]), "+f"(d[20]), "+f"(d[21]), "+f"(d[22]), "+f"(d[23]),
          "+f"(d[24]), "+f"(d[25]), "+f"(d[26]), "+f"(d[27]), "+f"(d[28]), "+f"(d[29]), "+f"(d[30]), "+f"(d[31])
        : "r"(a[0]), "r"(a[1]), "r"(a[2]), "r"(a[3]), "l"(db));
}

__device__ __forceinline__ int slice_at(int t, int r) { return t < 2 ? r ^ t : (t - 2) + ((t - 2) >= (r & 6) ? 2 : 0); }
__device__ __forceinline__ int oslice_at(int t, int r) {
    if (!OORDER) return slice_at(t, r);
    if (OORDER == 2) return t == 0 ? r : (t - 1) + ((t - 1) >= r ? 1 : 0);
    return t == 0 ? r : t < 5 ? 2 * (t - 1) + 1 - (r & 1) : 2 * (t - 5 + (t - 5 >= (r >> 1) ? 1 : 0)) + (r & 1);
}
__device__ __forceinline__ int main_col(int j) { return 80 * j + 16 * (j & 1); }
__device__ __forceinline__ int rem_col(int j) { return 80 * j + 64 - 64 * (j & 1); }
__device__ __forceinline__ int kstep(int odd, int u) { return u < 4 ? odd + u : 4 - 4 * odd; }
__device__ __forceinline__ int hsrc_at(int t, int r) {
    if (t < 2) return r;
    const int i = t < 5 ? t - 2 : t - 5;
    return 2 * (i + (i >= (r >> 1) ? 1 : 0)) + (r & 1);
}
__device__ __forceinline__ constexpr bool hpartB(int t) { return t == 1 || t >= 5; }

template <int NV> __device__ __forceinline__ bool bad_vecs(const uint32_t (&v)[NV][4], uint32_t tag) {
    uint32_t bad = 0;
#pragma unroll
    for (int u = 0; u < NV; u += 2) {
        if (u + 1 < NV) {
            uint32_t x;
            asm("lop3.b32 %0, %1, %2, %3, 0x7e;" : "=r"(x) : "r"(v[u][0]), "r"(v[u + 1][0]), "r"(tag));
            if (u == 0) bad = x; else asm("or.b32 %0, %0, %1;" : "+r"(bad) : "r"(x));
        } else {
            asm("lop3.b32 %0, %1, %2, %0, 0xbe;" : "+r"(bad) : "r"(v[u][0]), "r"(tag));
        }
    }
    return __any_sync(0xffffffffu, bad & 1);
}

struct Ctx {
    uint32_t sb, sb16;
    uint32_t rel_addr;
    char* mb;
    int r, warp, layer;
    int budget;
    uint32_t eall;
    __device__ __forceinline__ uint32_t lane16() const { return launder((uint32_t)(size_t)mb) & 511; }
    __device__ __forceinline__ int lane() const { return lane16() >> 4; }
    __device__ __forceinline__ uint32_t park() const { return sb + OFF_PARK + warp * 2560 + lane16(); }
    __device__ __forceinline__ const char* box(int src) const { return mb + launder(src - r) * RBOX; }
};
__device__ __forceinline__ void sched_fence(Ctx& c) {
    asm volatile("{.reg .pred p; setp.eq.s32 p, %0, 0x400000%=;\nFENCE_%=: @p nanosleep.u32 1; @p bra.uni FENCE_%=;}" :: "r"(c.eall) : "memory");
}
__device__ __forceinline__ void wait_full(Ctx& c, int k) { mbar_wait(c.sb + BAR_FULL + (k % NSLOT) * 8, (k / NSLOT) & 1, c.budget); }
__device__ __forceinline__ void release(const Ctx& c, int k) {
    if (c.rel_addr != 0 && (k < NITEMS_L - NSLOT || c.layer == 0)) mbar_arrive_cluster(c.rel_addr + (k % NSLOT) * 8);
}
template <int K> __device__ __forceinline__ void order_wait(Ctx& c) {
    if (((ORDER >> K) & 1) && c.warp >= 4) mbar_wait(c.sb + BAR_ORD + K * 8, c.layer, c.budget);
}
template <int K> __device__ __forceinline__ void order_post(const Ctx& c) {
    if (((ORDER >> K) & 1) && c.warp == 0 && c.rel_addr != 0) mbar_arrive(c.sb + BAR_ORD + K * 8);
}
template <int NV> __device__ __forceinline__ void ld_vecs(uint32_t (&v)[NV][4], const char* p, int v0) {
#pragma unroll
    for (int u = 0; u < NV; u++) ldv(v[u], p + voff(v0 + u));
}
template <int NV> __device__ __forceinline__ void publish(const Ctx& c, uint32_t (&v)[NV][4], int v0, uint32_t tag) {
#pragma unroll
    for (int u = 0; u < NV; u++) {
        v[u][0] = launder(tagged(v[u][0], tag));
        stv(c.mb + voff(v0 + u), v[u][0], v[u][1], v[u][2], v[u][3]);
    }
}
template <int NV, class F> __device__ __forceinline__ void check_vecs(Ctx& c, uint32_t (&v)[NV][4], uint32_t tag, F reload) {
    while (bad_vecs(v, tag) && --c.budget >= 0) reload();
}

__device__ __forceinline__ void probe(Ctx& c, int src, int vec) {
    const char* pp = c.mb + ((src - c.r) * RBOX - (int)c.lane16() + voff(vec) + 496);
    uint32_t v;
    do {
        asm volatile("ld.relaxed.gpu.global.u32 %0, [%1];" : "=r"(v) : "l"(pp) : "memory");
    } while (__any_sync(0xffffffffu, !(v & 1u)) && --c.budget >= 0);
}

__device__ __forceinline__ void park_x(const Ctx& c, const uint32_t (&v)[5][4]) {
    const uint32_t a = c.park();
#pragma unroll
    for (int u = 0; u < 5; u++) stsm4(a + u * 512, v[u][0], v[u][1], v[u][2], v[u][3]);
}
__device__ __forceinline__ void unpark_x(const Ctx& c, uint32_t (&v)[5][4]) {
    const uint32_t a = c.park();
#pragma unroll
    for (int u = 0; u < 5; u++) ldsm4(v[u], a + u * 512);
}
__device__ __forceinline__ void unstage(const Ctx& c, uint32_t (&v)[5][4], int odd) {
    const int lane = c.lane();
    const uint32_t a = c.sb + STAGE_OFF + (c.warp * 16 + (lane & 15)) * 336 + (lane >> 4) * 16;
#pragma unroll
    for (int u = 0; u < 5; u++) ldsm4(v[u], u < 4 ? a + odd * 192 + u * 32 : a + 128 + odd * 32);
}
__device__ __forceinline__ void pack_x(uint32_t (&X)[5][4], const float (&v)[40]) {
#pragma unroll
    for (int u = 0; u < 5; u++)
#pragma unroll
        for (int i = 0; i < 4; i++) X[u][i] = pack2(v[8 * u + 2 * i], v[8 * u + 2 * i + 1]);
}
__device__ __forceinline__ void unpack_x(float (&v)[40], const uint32_t (&X)[5][4]) {
#pragma unroll
    for (int u = 0; u < 5; u++)
#pragma unroll
        for (int i = 0; i < 4; i++) { v[8 * u + 2 * i] = bf_lo(X[u][i]); v[8 * u + 2 * i + 1] = bf_hi(X[u][i]); }
}
__device__ __forceinline__ void store_out(const Ctx& c, __nv_bfloat16* out) {
    __syncwarp();
    const int lane = c.lane();
    const uint32_t slot = c.sb + OFF_PARK + c.warp * 2560;
    const uint32_t sa = slot + (lane >> 4) * 512 + ((lane >> 3) & 1) * 256 + (lane & 7) * 16;
    __nv_bfloat16* ga = out + 2 * (lane & 7) * DM + main_col(c.r) + 8 * (lane >> 3);
    __nv_bfloat16* gb = out + 2 * (lane & 15) * DM + rem_col(c.r) + 8 * (lane >> 4);
#pragma unroll
    for (int i = 0; i < 5; i++) {
        uint4 v;
        asm volatile("ld.shared.v4.u32 {%0,%1,%2,%3}, [%4];" : "=r"(v.x), "=r"(v.y), "=r"(v.z), "=r"(v.w)
                     : "r"(i < 4 ? sa + (i >> 1) * 1024 + (i & 1) * 128 : slot + 2048 + lane * 16) : "memory");
        *reinterpret_cast<uint4*>(i < 4 ? ga + 16 * (i & 1) * DM + 32 * (i >> 1) : gb) = v;
    }
    __syncwarp();
}

template <int NB, int V0, uint32_t TAG> struct Gather {
    uint32_t buf[NB][5][4];
    __device__ __forceinline__ uint32_t (&at(int t))[5][4] { return buf[(t - 1) % NB]; }
    __device__ __forceinline__ void fetch(Ctx& c, int t) { ld_vecs(at(t), c.box(V0 == V_O ? oslice_at(t, c.r) : slice_at(t, c.r)), V0); }
    __device__ __forceinline__ void check(Ctx& c, int t) { check_vecs(c, at(t), TAG, [&]() { fetch(c, t); }); }
};

struct GQKV {
    float m[96], r[24];
    template <bool INIT> __device__ __forceinline__ void step(const uint32_t (&a)[5][4], uint32_t sb16, int off, int odd) {
#pragma unroll
        for (int u = 0; u < 5; u++) {
            const uint64_t dm = mkdesc(sb16 + kstep(odd, u) * 128, off, 10240, 1024, 1), dr = mkdesc(sb16 + kstep(odd, u) * 32, off + 30720, 2560, 256, 3);
            if (INIT && u == 0) { wgmma_n192_init(m, a[u], dm); wgmma_n48_init(r, a[u], dr); }
            else { wgmma_n192_acc(m, a[u], dm); wgmma_n48_acc(r, a[u], dr); }
        }
    }
};
struct GW1 {
    float m[112];
    template <bool INIT> __device__ __forceinline__ void step(const uint32_t (&a)[5][4], uint32_t sb16, int off, int odd) {
#pragma unroll
        for (int u = 0; u < 5; u++) {
            const uint64_t d = mkdesc(sb16 + kstep(odd, u) * 64, off, 5120, 512, 2);
            if (INIT && u == 0) wgmma_n224_init(m, a[u], d); else wgmma_n224_acc(m, a[u], d);
        }
    }
};

template <int K0, int LAST, uint32_t TAG, class G, class A, class Hook>
__device__ __forceinline__ void ln_head(G& g, A& a, Ctx& c, const uint32_t (&own)[5][4], const float (&xv)[40],
                                        float& rsA, float& rsB, uint32_t (&ax)[4], Hook hook, int tl0) {
    if ((PUBF >> (K0 ? 1 : 0)) & 1) sched_fence(c);
    wg_fence();
    g.template step<true>(own, c.sb16, slot_off(K0), c.r & 1);
    wg_commit();
    if (tl0) TL(tl0 + 1);
    sched_fence(c);
    if (!(LATE & 8)) hook(-1);
    float s[4] = {0.f, 0.f, 0.f, 0.f};
#pragma unroll
    for (int j = 0; j < 10; j++) {
        s[0] += xv[4 * j] + xv[4 * j + 1];
        s[1] = fmaf(xv[4 * j], xv[4 * j], fmaf(xv[4 * j + 1], xv[4 * j + 1], s[1]));
        s[2] += xv[4 * j + 2] + xv[4 * j + 3];
        s[3] = fmaf(xv[4 * j + 2], xv[4 * j + 2], fmaf(xv[4 * j + 3], xv[4 * j + 3], s[3]));
    }
    reg_fence(s);
    wait_full(c, K0 + 1);
    if (LATE & 8) hook(-1);
    a.check(c, 1);
    if (XPROBE == 1) hook(0);
    if (XPROBE != 2 || K0 != 0) a.fetch(c, 2);
    uint32_t sv[2][4];
    auto sfetch = [&]() {
        const int lane = c.lane();
        const char* p = c.mb + (((lane & 3) - c.r) * RBOX + (lane >> 2) * 16 - lane * 16);
        ldv(sv[0], p + voff(V_ST)); ldv(sv[1], p + voff(V_ST) + 4 * RBOX);
    };
#pragma unroll
    for (int t = 1; t <= LAST; t++) {
        if (FETCH_FENCE) sched_fence(c);
        if (tl0) TL(tl0 + 2 + t);
        wg_fence();
        g.template step<false>(a.at(t), c.sb16, slot_off(K0 + t), t == 1 ? (c.r & 1) ^ 1 : t & 1);
        wg_commit();
        if (XPROBE == 2 && K0 == 0 && t == 1) { sched_fence(c); hook(0); a.fetch(c, 2); }
        wg_wait<1>();
        release(c, K0 + t - 1);
        wait_full(c, K0 + t + 1);
        if (t == 1) {
#pragma unroll
            for (int i = 0; i < 4; i++) {
                s[i] += __shfl_xor_sync(0xffffffffu, s[i], 1);
                s[i] += __shfl_xor_sync(0xffffffffu, s[i], 2);
            }
            const int lane = c.lane();
            if ((lane & 3) == 0)
                stv(c.mb + voff(V_ST) - lane * 12, tagged(__float_as_uint(s[0]), TAG), __float_as_uint(s[1]), __float_as_uint(s[2]), __float_as_uint(s[3]));
            sched_fence(c);
        }
        a.check(c, t + 1);
        if (t == LAST) check_vecs(c, sv, TAG, sfetch);
        a.fetch(c, t + 2);
        if (t == LAST - 1) sfetch();
        hook(t);
    }
#pragma unroll
    for (int i = 0; i < 4; i++) {
        s[i] = __uint_as_float(sv[0][i]) + __uint_as_float(sv[1][i]);
        s[i] += __shfl_xor_sync(0xffffffffu, s[i], 1);
        s[i] += __shfl_xor_sync(0xffffffffu, s[i], 2);
    }
    const float mA = s[0] * (1.f / DM), mB = s[2] * (1.f / DM);
    rsA = rsq(fmaxf(fmaf(-mA, mA, s[1] * (1.f / DM)), 0.f) + LN_EPS);
    rsB = rsq(fmaxf(fmaf(-mB, mB, s[3] * (1.f / DM)), 0.f) + LN_EPS);
    const uint32_t h = pack2(mA, mB);
    const uint32_t l = pack2(mA - bf_lo(h), mB - bf_hi(h));
    const bool on = (c.lane16() & 32) == 0;
    ax[0] = on ? __byte_perm(h, l, 0x5410) : 0u;
    ax[1] = on ? __byte_perm(h, l, 0x7632) : 0u;
    ax[2] = 0u; ax[3] = 0u;
    asm volatile("" : "+r"(ax[0]), "+r"(ax[1]), "+r"(ax[2]), "+r"(ax[3]), "+f"(rsA), "+f"(rsB));
    sched_fence(c);
}

__global__ void __cluster_dims__(2, 1, 1) __launch_bounds__(384, 1)
fused_layers_kernel(const __grid_constant__ Params prm, const __grid_constant__ CUtensorMap tmQM, const __grid_constant__ CUtensorMap tmQR,
                    const __grid_constant__ CUtensorMap tmWO, const __grid_constant__ CUtensorMap tmW1a, const __grid_constant__ CUtensorMap tmW1b,
                    const __grid_constant__ CUtensorMap tmW2, const __grid_constant__ CUtensorMap tmW2a) {
    extern __shared__ __align__(1024) uint8_t smem_raw[];
    const uint32_t sb = smem_u32(smem_raw);
    const int warp = __shfl_sync(0xffffffffu, threadIdx.x >> 5, 0);
    const int lane = threadIdx.x & 31;
    const int cl = prm.role[blockIdx.x >> 1], p = blockIdx.x & 1;
    const int r = cl & 7, blk = (cl >> 3) * 2 + p;
    const int role = blk * 8 + r;
    TL(0); TLINIT

    if (PFW && warp >= 10 && lane < 15 * PFW) {
        const int l15 = lane >= 15 ? lane - 15 : lane, row = (l15 * 11) >> 5;
        const char* wp = reinterpret_cast<const char*>(prm.wqkv + (80 * slice_at(warp - 10 + (lane >= 15 ? 2 : 0), r) + 5 * blk + row) * DQKV + 640 * (l15 - 3 * row) + 80 * r);
#pragma unroll
        for (int i = 0; i < 5; i++) asm volatile("prefetch.global.L2 [%0];" :: "l"(wp + i * 32));
    }
    if (warp >= 8 && elect_one()) {
        if (warp == 8) { prefetch_map(&tmQM); prefetch_map(&tmQR); }
        if (warp == 9) {
#pragma unroll
            for (int i = 0; i < NSLOT; i++) { mbar_init(sb + BAR_FULL + i * 8, 1); mbar_init(sb + BAR_EMPTY + i * 8, 16); }
            mbar_init(sb + BAR_STAGE, 16);
            mbar_init(sb + BAR_CS, 3); mbar_init(sb + BAR_CS + 8, 3);
#pragma unroll
            for (int i = 0; i < NORD; i++) mbar_init(sb + BAR_ORD + i * 8, 2);
            asm volatile("fence.mbarrier_init.release.cluster;" ::: "memory");
        }
    }
    __syncwarp();
    asm volatile("barrier.cluster.arrive.relaxed.aligned;" ::: "memory");
    uint32_t etag0;
    asm volatile("ld.relaxed.gpu.global.u32 %0, [%1];" : "=r"(etag0) : "l"(prm.scr + (uint32_t)(G_EPOCH + role * 128 + lane * 4)) : "memory");
    if (XPROBE && warp < 8) stv(prm.scr + (uint32_t)(blk * BBOX + r * RBOX + warp * WBOX + lane * 16 + voff(V_X + 4)), 0u, 0u, 0u, 0u);
    auto load_x = [&]() {
    if (warp < 8 && lane < 20) {
        const char* xr = reinterpret_cast<const char*>(prm.xin + (size_t)(128 * blk + 32 * (warp & 3) + (warp >> 2)) * DM + 160 * (r >> 1)) + lane * 16;
#pragma unroll
        for (int i = 0; i < 16; i++)
            asm volatile("cp.async.cg.shared.global [%0], [%1], 16;" :: "r"(sb + STAGE_OFF + (warp * 16 + i) * 336 + lane * 16), "l"(xr + i * 4 * DM) : "memory");
    }
    };
    if (XPF && warp < 8) {
        const char* xr = reinterpret_cast<const char*>(prm.xin + (size_t)(128 * blk + 32 * (warp & 3) + (warp >> 2) + 2 * (lane & 15)) * DM + 80 * r) + (lane >> 4) * 32;
        asm volatile("prefetch.global.L2 [%0];" :: "l"(xr));
        asm volatile("prefetch.global.L2 [%0];" :: "l"(xr + 64));
        if (lane < 16) asm volatile("prefetch.global.L2 [%0];" :: "l"(xr + 128));
    }
    if (!XL) load_x();
    TL(10);
    asm volatile("barrier.cluster.wait.aligned;" ::: "memory");
    if (warp == 8) {
        TL(1);
        if (elect_one()) {
#pragma unroll 1
            for (int i = 0; i < 2; i++) {
                const uint32_t base = sb + i * slot_off(1), bar = sb + BAR_FULL + i * 8;
                const int row = 80 * (r ^ i);
                mbar_expect(bar, 38400);
                tma2d_mc(base + p * 10240, &tmQM, main_col(r) + 640 * p, row, bar);
                if (p) tma2d_mc(base + 20480, &tmQM, main_col(r) + 1280, row, bar);
                else tma3d_mc(base + 30720, &tmQR, rem_col(r), row, 0, bar);
            }
        }
        __syncwarp();
        TL(2);
    }

    if (warp >= 8) {
        int budget = SPIN_BUDGET;
        asm volatile("setmaxnreg.dec.sync.aligned.u32 %0;" :: "n"(REG_HELP));
        if (warp == 8) {
            TL(5);
            if (elect_one()) {
                int slot = 2, use = 0;
#pragma unroll 1
                for (int i = 2; i < NITEMS; i++) {
                    const int k = i >= NITEMS_L ? i - NITEMS_L : i;
                    const uint32_t base = sb + slot_off(slot), bar = sb + BAR_FULL + slot * 8;
                    if (use > 0) mbar_wait(sb + BAR_EMPTY + slot * 8, (use - 1) & 1, budget);
                    if (i == 3) mbar_wait(sb + BAR_STAGE, 0, budget);
                    if (PAUSE && k == IT_W1 + 1) mbar_wait(sb + BAR_EMPTY + ((IT_WO + PAUSE) % 5) * 8, use & 1, budget);
                    if (i < INFL_UNTIL) mbar_wait(sb + BAR_FULL + (slot >= 2 ? slot - 2 : slot + 3) * 8, (slot >= 2 ? use : use - 1) & 1, budget);
                    const int q = (k + p) & 1;
                    if (k < 8) {
                        const int np = k < 5 ? 3 : 2, row = 80 * slice_at(k, r), col = main_col(r) + 640 * (3 - np);
                        mbar_expect(bar, np * 10240 + 7680);
                        if (q) {
                            tma2d_mc(base, &tmQM, col, row, bar);
                            tma2d_mc(base + 10240, &tmQM, col + 640, row, bar);
                        } else {
                            if (np == 3) tma2d_mc(base + 20480, &tmQM, col + 1280, row, bar);
                            tma3d_mc(base + np * 10240, &tmQR, rem_col(r), row, 0, bar);
                        }
                    } else if (k == 8) {
                        mbar_expect(bar, 30720);
                        tma2d_mc(base + q * 10240, &tmQM, main_col(r), 80 * slice_at(5 + q, r), bar);
                        if (!q) tma2d_mc(base + 20480, &tmQM, main_col(r), 80 * slice_at(7, r), bar);
                    } else if (k < IT_W1) {
                        mbar_expect(bar, 30720);
                        const int row = 80 * oslice_at(2 * (k - IT_WO) + p, r);
#pragma unroll
                        for (int a = 0; a < 3; a++) tma2d_mc(base + p * 15360 + a * 5120, &tmWO, a < 2 ? main_col(r) + 32 * a : rem_col(r), row, bar);
                    } else if (k < IT_W2) {
                        const bool full = k < IT_W1 + 6, pb = full ? q : k == IT_W1 + 7;
                        mbar_expect(bar, full ? 35840 : pb ? 40960 : 30720);
                        const int row = 80 * slice_at(full ? k - IT_W1 : 6 + p, r);
                        if (pb) tma3d_mc(base + (full ? 0 : p * 20480), &tmW1b, 0, row, 7 * r, bar);
                        else tma3d_mc(base + (full ? 20480 : p * 15360), &tmW1a, 0, row, 7 * r + 4, bar);
                    } else if (k < IT_W2 + 8) {
                        const int st = k - IT_W2, a0 = st < 6 ? 0 : 2;
                        const bool pb = hpartB(st);
                        const int atom = pb ? 8192 : 6144;
                        mbar_expect(bar, (5 - a0) * atom);
                        const int row = 224 * hsrc_at(st, r) + (pb ? 0 : 128);
#pragma unroll 1
                        for (int a = a0 + q; a < 5; a += 2)
                            tma2d_mc(base + (a - a0) * atom, pb ? &tmW2 : &tmW2a, a < 4 ? main_col(r ^ (a >> 1)) + 32 * (a & 1) : 160 * (r >> 1) + 64, row, bar);
                    } else {
                        mbar_expect(bar, 32768);
                        const int row = 224 * hsrc_at(6 + p, r);
                        tma2d_mc(base + p * 16384, &tmW2, main_col(r), row, bar);
                        tma2d_mc(base + p * 16384 + 8192, &tmW2, main_col(r) + 32, row, bar);
                    }
                    if (i == 2) TL(3);
                    if (i == 3) { prefetch_map(&tmWO); prefetch_map(&tmW1a); prefetch_map(&tmW1b); prefetch_map(&tmW2); prefetch_map(&tmW2a); }
                    if (++slot == NSLOT) { slot = 0; use++; }
                }
            }
            __syncwarp();
            TLDUMP(16);
        } else {
#pragma unroll 1
            for (int i = threadIdx.x - 288; i < XTRA_BYTES / 16; i += 96)
                asm volatile("st.shared.v4.u32 [%0], {%1,%1,%1,%1};" :: "r"(sb + OFF_XQM + i * 16), "r"(0) : "memory");
            asm volatile("bar.sync 5, 96;" ::: "memory");
            const uint32_t etag = (launder(etag0) & 1u) ^ 1u;
            if (lane < 10) {
                char* cs = prm.scr + (uint32_t)(G_CS + (r * 6 + warp - 9) * 5120 + blk * 320 + lane * 32);
#pragma unroll
                for (int i = 0; i < 4; i++) stv(cs + (i >> 1) * 3 * 5120 + (i & 1) * 16, etag ^ 1u, 0u, 0u, 0u);
            }
            if (CS_GATE == 1) mbar_wait(sb + BAR_FULL, 0, budget);
            if (CS_GATE > 1) __nanosleep(CS_GATE);
            TLH(11);
#pragma unroll 1
            for (int mat = 0; mat < 2; mat++) {
                const int lane = launder(threadIdx.x & 31), j = launder(warp) - 9;
                const int rp = lane < 30 ? (lane * 13) >> 7 : 2, ch = lane < 30 ? lane - 10 * rp : 0;
                const int col = mat ? 224 * r + 80 * j + 8 * ch : 640 * j + 80 * r + 8 * ch;
                const bool valid = !mat || (10 * j + ch < 28 && col < DFF);
                float a[8] = {0.f, 0.f, 0.f, 0.f, 0.f, 0.f, 0.f, 0.f};
                auto sum_rows = [&](const __nv_bfloat16* w0, auto pitch_c) {
                    constexpr int PITCH = decltype(pitch_c)::value;
                    const char* src = reinterpret_cast<const char*>(w0 + (40 * blk + rp) * PITCH + (valid ? col : 0));
#pragma unroll 1
                    for (int h = 0; h < 2; h++) {
                        uint32_t w[7][4];
                        const bool last = h == 0 || rp == 0;
#pragma unroll
                        for (int i = 0; i < 6; i++) ldv(w[i], src + i * 6 * PITCH);
                        ldv(w[6], src + (last ? 36 * PITCH : 0));
#pragma unroll
                        for (int i = 0; i < 7; i++)
#pragma unroll
                            for (int e = 0; e < 4; e++) {
                                const uint32_t v = (i < 6 || last) ? w[i][e] : 0u;
                                a[2 * e] += bf_lo(v); a[2 * e + 1] += bf_hi(v);
                            }
                        src += 42 * PITCH;
                    }
                };
                if (mat == 0) {
                    sum_rows(prm.wqkv, IntC<DQKV>());
                } else {
                    sum_rows(prm.w1, IntC<DFF>());
                }
                char* cs = prm.scr + (uint32_t)(G_CS + ((r * 2 + mat) * 3 + j) * 5120);
#pragma unroll
                for (int i = 0; i < 8; i++) {
                    a[i] += __shfl_down_sync(0xffffffffu, a[i], 10) + __shfl_down_sync(0xffffffffu, a[i], 20);
                    a[i] = valid ? a[i] : 0.f;
                }
                if (lane < 10) {
                    char* dst = cs + blk * 320 + lane * 32;
                    stv(dst, tagged(__float_as_uint(a[0]), etag), __float_as_uint(a[1]), __float_as_uint(a[2]), __float_as_uint(a[3]));
                    stv(dst + 16, tagged(__float_as_uint(a[4]), etag), __float_as_uint(a[5]), __float_as_uint(a[6]), __float_as_uint(a[7]));
                }
                if (mat == 0) {
                    TLH(12);
                    const int c1 = 224 * r + 80 * j + 8 * ch;
                    if (10 * j + ch < 28 && c1 < DFF) {
#pragma unroll 1
                        for (int i = rp; i < 40; i += 3) asm volatile("prefetch.global.L2 [%0];" :: "l"(prm.w1 + (40 * blk + i) * DFF + c1));
                    }
                    __syncwarp();
                }
                cs += (lane < 20 ? lane : 0) * 16;
                a[0] = 0.f; a[1] = 0.f; a[2] = 0.f; a[3] = 0.f;
#pragma unroll 1
                for (int b0 = 0; b0 < 2;) {
                    uint32_t v[8][4];
#pragma unroll
                    for (int i = 0; i < 8; i++) ldv(v[i], cs + i * 320);
                    if (bad_vecs(v, etag) && --budget >= 0) continue;
#pragma unroll
                    for (int i = 0; i < 8; i++)
#pragma unroll
                        for (int e = 0; e < 4; e++) a[e] -= __uint_as_float(v[i][e]);
                    b0++;
                    cs += 8 * 320;
                }
                if (mat == 0) TLH(14);
                const uint32_t h0 = pack2(a[0], a[1]), h1 = pack2(a[2], a[3]);
                const uint32_t l0 = pack2(a[0] - bf_lo(h0), a[1] - bf_hi(h0)), l1 = pack2(a[2] - bf_lo(h1), a[3] - bf_hi(h1));
                const int cc = 4 * launder(lane), cm = cc - 16 * (r & 1), cw = 80 * j + cc;
                const bool mainp = cm >= 0 && cm < 64;
                const uint32_t sh = mat ? 6 : mainp ? 7 : 5;
                const uint32_t ad = sb + (mat ? OFF_XW1 + (cw >> 5) * 512 + (cw & 31) * 2 : mainp ? OFF_XQM + j * 1024 + cm * 2 : OFF_XQR + j * 256 + (cc & 15) * 2);
                if (cc < 80 && (!mat || cw < 224)) {
#pragma unroll
                    for (int row = 0; row < 4; row++) {
                        const uint32_t o = row << sh;
                        asm volatile("st.shared.v2.u32 [%0], {%1,%2};" :: "r"((ad + o) ^ ((o >> 7) << 4)), "r"(row < 2 ? h0 : l0), "r"(row < 2 ? h1 : l1) : "memory");
                    }
                }
                asm volatile("fence.proxy.async.shared::cta;" ::: "memory");
                __syncwarp();
                if (lane == 0) mbar_arrive(sb + BAR_CS + mat * 8);
                TLH(6 + mat);
            }
        }
    } else {
        if (XL > 1) __nanosleep(XL);
        if (XL) load_x();
        TL(11);
        asm volatile("cp.async.wait_all;" ::: "memory");
        TL(12);
        __syncwarp();
        asm volatile("setmaxnreg.inc.sync.aligned.u32 %0;" :: "n"(REG_CONS));
        TL(14);
        Ctx c;
        c.sb = sb; c.sb16 = (sb & 0x3FFFF) >> 4; c.r = r; c.warp = warp; c.layer = 0; c.budget = SPIN_BUDGET; c.eall = __ballot_sync(0xffffffffu, !(launder(etag0) & 1u));
        c.mb = reinterpret_cast<char*>(__shfl_sync(0xffffffffu, reinterpret_cast<size_t>(prm.scr + (uint32_t)(blk * BBOX + r * RBOX + warp * WBOX + lane * 16)), lane));
        asm volatile("mapa.shared::cluster.u32 %0, %1, %2;" : "=r"(c.rel_addr) : "r"(sb + BAR_EMPTY), "r"(lane & 1));
        c.rel_addr = __shfl_sync(0xffffffffu, lane < 2 ? c.rel_addr : 0, lane);
        uint32_t X[5][4];
        float xv[40];
        unstage(c, X, r & 1);
        wait_full(c, 0);
        TL(13);
        unpack_x(xv, X);
        park_x(c, X);
        TL(1);

        const int r_ = r, blk_ = blk, warp_ = warp;
#define PHASE_IDS const int r = launder(r_), blk = launder(blk_), warp = launder(warp_), wg = warp >> 2, w = warp & 3; \
                  c.r = r; c.warp = warp; c.sb = launder(sb); c.sb16 = (c.sb & 0x3FFFF) >> 4; const uint32_t etag = launder(c.eall) & 1u; (void)etag; (void)blk; (void)wg; (void)w;
#pragma unroll 1
        for (int layer = 0;; layer++) {
            c.layer = layer;
            float rsA, rsB;
            uint32_t O[5][4];
            {
                PHASE_IDS
                GQKV q;
                Gather<3, V_X, 1u> ga;
                uint32_t ax[4];
                auto hook = [&](int st) {
                    if (st == -1) {
                        if (layer == 0) {
                            unstage(c, ga.buf[0], (r & 1) ^ 1);
#pragma unroll
                            for (int u = 0; u < 5; u++) ga.buf[0][u][0] |= 1u;
                            if (c.rel_addr != 0) mbar_arrive_cluster(c.rel_addr + (BAR_STAGE - BAR_EMPTY));
                        } else {
                            ga.fetch(c, 1);
                        }
                    }
                    if (st == 0 && layer == 0) probe(c, c.lane() & 7, V_X + 4);
                    if (st >= 1 && layer == 0) {
                        if (st == CLR_HALO && w == 3) {
#pragma unroll
                            for (int u = 0; u < 6; u++) stv(c.mb + voff(V_HALO + u), etag ^ 1u, 0u, 0u, 0u);
                        }
#pragma unroll
                        for (int u = 0; u < 5; u++)
                            if (st == ((CLR_O >> (4 * u)) & 15)) stv(c.mb + voff(V_O + u), 0u, 0u, 0u, 0u);
                    }
                };
                publish(c, X, V_X, 1u);
                ln_head<0, 4, 1u>(q, ga, c, X, xv, rsA, rsB, ax, hook, (TLSEL == 1 + layer * 4) ? 50 : 0);
                float qm[32], kv[64];
                wg_wait<0>();
                reg_fence(q.m);
                rename<32, 0>(qm, q.m);
                rename<64, 32>(kv, q.m);
#pragma unroll
                for (int st = 5; st < 8; st++) {
                    if (st == 7) order_wait<0>(c);
                    wg_fence();
#pragma unroll
                    for (int u = 0; u < 5; u++) {
                        wgmma_n128_acc(kv, ga.at(st)[u], mkdesc(c.sb16, slot_off(st) + kstep(st & 1, u) * 2048, 10240, 1024, 1));
                        wgmma_n48_acc(q.r, ga.at(st)[u], mkdesc(c.sb16, slot_off(st) + 20480 + kstep(st & 1, u) * 512, 2560, 256, 3));
                    }
                    if (st == 7) {
                        wgmma_n128_acc(kv, ax, mkdesc(c.sb16, OFF_XQM + 1024, 1024, 0, 1));
                        wgmma_n48_acc(q.r, ax, mkdesc(c.sb16, OFF_XQR, 256, 0, 3));
                    }
                    wg_commit();
                    if (st == 7) order_post<0>(c);
                    if (st > 5) wg_wait<1>();
                    release(c, st - 1);
                    wait_full(c, st + 1);
                    if (st == 5) {
                        ga.check(c, 6);
                        ga.fetch(c, 7);
                        if (FETCH_FENCE) sched_fence(c);
                    }
                    if (st == 6) {
                        if (layer == 0) mbar_wait(c.sb + BAR_CS, 0, c.budget);
                        ga.check(c, 7);
                    }
                }
                float rk1[2], rk2[2];
                {
                    const int t8 = (c.lane16() >> 1) & 24;
#pragma unroll
                    for (int e = 0; e < 2; e++) {
                        rk2[e] = __shfl_sync(0xffffffffu, rsB, t8 + 4 * e);
                        rk1[e] = __shfl_sync(0xffffffffu, rsA, t8 + 4 * e);
                    }
                }
                auto q_steps = [&](int n0, int n1) {
                    wg_fence();
#pragma unroll
                    for (int n = n0; n < n1; n++) {
                        if (n < 15) wgmma_n64_acc(qm, ga.at(5 + n / 5)[n % 5], mkdesc(c.sb16, slot_off(8) + (n / 5 * 5 + kstep((5 + n / 5) & 1, n % 5)) * 2048, 1024, 1024, 1));
                        else wgmma_n64_acc(qm, ax, mkdesc(c.sb16, OFF_XQM, 1024, 0, 1));
                    }
                    wg_commit();
                };
                q_steps(0, 7);
                wg_wait<1>();
                reg_fence(kv);
                reg_fence(q.r);
                release(c, 7);
                TL(2 + layer * 16);
                uint32_t T[3][10][2];
                auto pack_tiles = [&](int pc, int h, bool odd) {
#pragma unroll
                    for (int j = 0; j < 10; j++) {
                        const bool isrem = odd ? j < 2 : j >= 8;
                        const int e = isrem ? pc * 8 + 4 * (j & 1) + 2 * h : 4 * ((odd ? j + 6 : j) & 7) + 2 * h;
                        if (isrem) T[pc][j][h] = pack2(q.r[e], q.r[e + 1]);
                        else T[pc][j][h] = pc == 0 ? pack2(qm[e], qm[e + 1]) : pack2(kv[(pc - 1) * 32 + e], kv[(pc - 1) * 32 + e + 1]);
                    }
                };
                if (r & 1) { pack_tiles(1, 1, true); pack_tiles(2, 1, true); }
                else { pack_tiles(1, 1, false); pack_tiles(2, 1, false); }
                auto hreg = [&](int n) -> uint32_t& { return n < 8 ? T[1][n + (n + 2) / 4][1] : n < 10 ? T[1][5 * n - 38][1] : T[2][n - 10][1]; };
                if (w == 3) {
                    char* hg = c.mb + layer * (2 * PLANE);
#pragma unroll
                    for (int u = 0; u < 5; u++) {
                        hreg(4 * u) = tagged(hreg(4 * u), etag);
                        stv(hg + voff(V_HALO + u), hreg(4 * u), hreg(4 * u + 1), hreg(4 * u + 2), hreg(4 * u + 3));
                    }
                    stv(hg + voff(V_HALO + 5), tagged(__float_as_uint(rk2[0]), etag), __float_as_uint(rk2[1]), 0u, 0u);
                }
                if (r & 1) { pack_tiles(1, 0, true); pack_tiles(2, 0, true); }
                else { pack_tiles(1, 0, false); pack_tiles(2, 0, false); }
                unpark_x(c, X);
                q_steps(7, 16);
                if (w < 3) {
                    const uint32_t hs = c.park();
#pragma unroll
                    for (int u = 0; u < 5; u++) stsm4(hs + u * 512, hreg(4 * u), hreg(4 * u + 1), hreg(4 * u + 2), hreg(4 * u + 3));
                    if (c.lane16() < 64) asm volatile("st.shared.v2.f32 [%0], {%1,%2};" :: "r"(c.sb + OFF_RK + warp * 32 + (c.lane16() >> 1)), "f"(rk2[0]), "f"(rk2[1]) : "memory");
                }
                asm volatile("bar.sync %0, 128;" :: "r"(1 + wg) : "memory");
                uint32_t H[6][4];
                auto hfetch = [&]() { ld_vecs(H, c.mb + (3 * WBOX - BBOX) + layer * (2 * PLANE), V_HALO); };
                if (w > 0) {
                    const uint32_t hs = c.park() - 2560;
                    ldsm4(H[0], hs); ldsm4(H[1], hs + 512);
                    asm volatile("ldmatrix.sync.aligned.m8n8.x2.shared.b16 {%0,%1}, [%2];" : "=r"(H[2][0]), "=r"(H[2][1]) : "r"(hs + 1024) : "memory");
                    asm volatile("ldmatrix.sync.aligned.m8n8.x2.trans.shared.b16 {%0,%1}, [%2];" : "=r"(H[2][2]), "=r"(H[2][3]) : "r"(hs + 1280) : "memory");
                    ldsm4t(H[3], hs + 1536); ldsm4t(H[4], hs + 2048);
                    asm volatile("ld.shared.v2.u32 {%0,%1}, [%2];" : "=r"(H[5][0]), "=r"(H[5][1]) : "r"(c.sb + OFF_RK + warp * 32 - 32 + ((c.lane16() >> 1) & 24)) : "memory");
                    H[5][2] = 0u; H[5][3] = 0u;
                } else if (blk > 0) {
                    hfetch();
                } else {
#pragma unroll
                    for (int u = 0; u < 6; u++) { H[u][0] = 0u; H[u][1] = 0u; H[u][2] = 0u; H[u][3] = 0u; }
                }
                auto hK = [&](int j) { return j == 2 ? H[2][0] : j == 7 ? H[2][1] : H[(j - (j + 2) / 5) >> 2][(j - (j + 2) / 5) & 3]; };
                auto hV = [&](int j) { return H[(j + 10) >> 2][(j + 10) & 3]; };
                uint32_t Vt1[10], Vt2[10];
#pragma unroll
                for (int j = 0; j < 10; j++) { Vt1[j] = movm(T[2][j][0]); Vt2[j] = movm(T[2][j][1]); }
                wg_wait<0>();
                reg_fence(qm);
                release(c, 8);
                if (r & 1) { pack_tiles(0, 0, true); pack_tiles(0, 1, true); }
                else { pack_tiles(0, 0, false); pack_tiles(0, 1, false); }
                TL(3 + layer * 16);
                const int g = c.lane() >> 2, t = c.lane() & 3;
                const bool sel0 = 2 * t > g, sel1 = 2 * t + 1 > g;
                const float cs = 0.22360679774997896f * 1.4426950408889634f;
                const float kB0 = sel0 ? rk1[0] : rk2[0], kB1 = sel1 ? rk1[1] : rk2[1];
                const float fB0 = rsB * cs * kB0, fB1 = rsB * cs * kB1;
                float lA0[4], lA1[4], lB0[4], lB1[4];
                uint32_t qs[4][2];
#pragma unroll
                for (int h = 0; h < 4; h++) {
                    const int f0 = 5 * (h >> 1) + 3 * (h & 1), f1 = f0 + 1, s = 5 * (h >> 1) + 2;
                    const bool keep = (h & 1) ? (t >= 2) : (t < 2);
                    qs[h][0] = keep ? T[0][s][0] : 0u; qs[h][1] = keep ? T[0][s][1] : 0u;
                    float s1[4], s2[4];
                    mma_k8_init(s1, qs[h][0], qs[h][1], T[1][s][0]);
                    mma_k8_init(s2, qs[h][0], qs[h][1], T[1][s][1]);
                    mma_k16_acc(s1, T[0][f0][0], T[0][f0][1], T[0][f1][0], T[0][f1][1], T[1][f0][0], T[1][f1][0]);
                    mma_k16_acc(s2, T[0][f0][0], T[0][f0][1], T[0][f1][0], T[0][f1][1], T[1][f0][1], T[1][f1][1]);
                    lA0[h] = s1[0]; lA1[h] = s1[1];
                    lB0[h] = (sel0 ? s1[2] : s2[2]) * fB0;
                    lB1[h] = (sel1 ? s1[3] : s2[3]) * fB1;
                }
                wait_full(c, IT_WO);
                if (w == 0 && blk > 0) {
                    check_vecs(c, H, etag, hfetch);
#pragma unroll
                    for (int n = 10; n < 20; n++) H[n >> 2][n & 3] = movm(H[n >> 2][n & 3]);
                }
                const bool first = (blk == 0) && (w == 0);
                const float kA0 = sel0 ? __uint_as_float(H[5][0]) : rk1[0], kA1 = sel1 ? __uint_as_float(H[5][1]) : rk1[1];
                const float fA0 = rsA * cs * kA0, fA1 = rsA * cs * kA1;
                const float bA0 = (first && sel0) ? -INFINITY : 0.f, bA1 = (first && sel1) ? -INFINITY : 0.f;
                const uint32_t M = (sel0 ? 0x0000ffffu : 0u) | (sel1 ? 0xffff0000u : 0u);
#pragma unroll
                for (int h = 0; h < 4; h++) {
                    const int f0 = 5 * (h >> 1) + 3 * (h & 1), f1 = f0 + 1, s = 5 * (h >> 1) + 2;
                    float s0[4];
                    mma_k8_init(s0, qs[h][0], qs[h][1], hK(s));
                    mma_k16_acc(s0, T[0][f0][0], T[0][f0][1], T[0][f1][0], T[0][f1][1], hK(f0), hK(f1));
                    lA0[h] = fmaf(sel0 ? s0[0] : lA0[h], fA0, bA0);
                    lA1[h] = fmaf(sel1 ? s0[1] : lA1[h], fA1, bA1);
                }
                uint32_t pA[4], pB[4];
#pragma unroll
                for (int h = 0; h < 4; h++) {
                    float mA = fmaxf(lA0[h], lA1[h]), mB = fmaxf(lB0[h], lB1[h]);
                    mA = fmaxf(mA, __shfl_xor_sync(0xffffffffu, mA, 1));
                    mB = fmaxf(mB, __shfl_xor_sync(0xffffffffu, mB, 1));
                    mA = fmaxf(mA, __shfl_xor_sync(0xffffffffu, mA, 2));
                    mB = fmaxf(mB, __shfl_xor_sync(0xffffffffu, mB, 2));
                    const float eA0 = ex2(lA0[h] - mA), eA1 = ex2(lA1[h] - mA), eB0 = ex2(lB0[h] - mB), eB1 = ex2(lB1[h] - mB);
                    float sA = eA0 + eA1, sB = eB0 + eB1;
                    sA += __shfl_xor_sync(0xffffffffu, sA, 1);
                    sB += __shfl_xor_sync(0xffffffffu, sB, 1);
                    sA += __shfl_xor_sync(0xffffffffu, sA, 2);
                    sB += __shfl_xor_sync(0xffffffffu, sB, 2);
                    const float iA = rcp(sA), iB = rcp(sB);
                    pA[h] = pack2(eA0 * kA0 * iA, eA1 * kA1 * iA);
                    pB[h] = pack2(eB0 * kB0 * iB, eB1 * kB1 * iB);
                }
#pragma unroll
                for (int h = 0; h < 4; h++) {
                    const int f0 = 5 * (h >> 1) + 3 * (h & 1), s = 5 * (h >> 1) + 2;
                    const uint32_t ap = pA[h] & M, a0 = pA[h] & ~M, a1 = pB[h] & M, a3 = pB[h] & ~M;
#pragma unroll
                    for (int i = 0; i < 3; i++) {
                        const int j = i < 2 ? f0 + i : s;
                        float o[4];
                        mma_k8_init(o, ap, 0u, hV(j));
                        mma_k16_acc(o, a0, a1, 0u, a3, Vt1[j], Vt2[j]);
                        const uint32_t o0 = pack2(o[0], o[1]), o1 = pack2(o[2], o[3]);
                        uint32_t& d0 = O[j >> 1][2 * (j & 1)];
                        uint32_t& d1 = O[j >> 1][2 * (j & 1) + 1];
                        if (i < 2 || (h & 1) == 0) { d0 = o0; d1 = o1; }
                        else { d0 = t >= 2 ? o0 : d0; d1 = t >= 2 ? o1 : d1; }
                    }
                }
                publish(c, O, V_O, 1u);
            }
            TL(4 + layer * 16);
            {
                PHASE_IDS
                Gather<7, V_O, 1u> ga;
                sched_fence(c);
                if (WO_EARLY) {
#pragma unroll
                    for (int i = 1; i <= WO_B1; i++) ga.fetch(c, i);
                }
                unpack_x(xv, X);
#pragma unroll
                for (int st = 0; st < 8; st++) {
                    if (st == 6) order_wait<1>(c);
                    wg_fence();
#pragma unroll
                    for (int u = 0; u < 5; u++)
                        wgmma_n80_acc(xv, st == 0 ? O[u] : ga.at(st > 0 ? st : 1)[u], mkdesc(c.sb16, slot_off(IT_WO + st / 2) + (st & 1) * 15360 + u * 1024, 5120, 512, 2));
                    wg_commit();
                    if (st == 7) order_post<1>(c);
                    if (st > 0 && (st & 1) == 0) { wg_wait<1>(); release(c, IT_WO + st / 2 - 1); }
                    if ((LATE & 1) && st == 0) wg_wait<0>();
                    const bool batch = st == 0 || st == WO_B1 || st == WO_B2;
                    if (st & 1) wait_full(c, IT_WO + st / 2 + 1); else if (batch) sched_fence(c);
                    if (!WO_EARLY && st == 0) {
#pragma unroll
                        for (int i = 1; i <= WO_B1; i++) ga.fetch(c, i);
                    }
                    if (batch) {
                        const int e0 = st == 0 ? WO_B1 : st == WO_B1 ? WO_B2 : 7, e1 = st == 0 ? WO_B2 : 7;
#pragma unroll
                        for (int i = st + 1; i <= e0; i++) ga.check(c, i);
#pragma unroll
                        for (int i = e0 + 1; i <= e1; i++) ga.fetch(c, i);
                        if (FETCH_FENCE && e1 > e0) sched_fence(c);
                    }
                    if (TLSEL == 2 + layer * 4) TL(50 + st);
                }
                wg_wait<0>();
                reg_fence(xv);
                release(c, IT_W1 - 1);
                TL(5 + layer * 16);
                pack_x(X, xv);
                park_x(c, X);
                if (DBG_STAGE == 1 + 2 * layer) store_out(c, prm.out + (size_t)(128 * blk + 32 * w + wg) * DM);
                publish(c, X, V_X, 0u);
            }
            TL(6 + layer * 16);
            {
                PHASE_IDS
                const uint32_t ltag = layer ^ 1u;
                uint32_t Ha[6][4], Hb[8][4];
                {
                    GW1 f;
                    Gather<3, V_X, 0u> ga;
                    uint32_t ax[4];
                    ln_head<IT_W1, 5, 0u>(f, ga, c, X, xv, rsA, rsB, ax, [&](int st) {
                        if (st == -1) ga.fetch(c, 1);
                        if (st == 2 && layer == 0) {
                            stv(c.mb + voff(V_HB + 7), 0u, 0u, 0u, 0u);
                            stv(c.mb + voff(V_HA + 5), 0u, 0u, 0u, 0u);
                        }
                        if (st == 3 && layer == 0 && w == 3) {
#pragma unroll
                            for (int u = 0; u < 6; u++) stv(c.mb + voff(V_HALO + 10 + u), etag ^ 1u, 0u, 0u, 0u);
                        }
                    }, (TLSEL == 3 + layer * 4) ? 50 : 0);
                    float fa[48], fb[64];
                    if (layer == 0) mbar_wait(c.sb + BAR_CS + 8, 0, c.budget);
                    order_wait<2>(c);
                    wg_wait<0>();
                    reg_fence(f.m);
                    rename<64, 0>(fb, f.m);
                    rename<48, 64>(fa, f.m);
#pragma unroll
                    for (int st = 6; st < 8; st++) {
                        wg_fence();
#pragma unroll
                        for (int u = 0; u < 5; u++)
                            wgmma_n96_acc(fa, ga.at(st)[u], mkdesc(c.sb16, slot_off(IT_W1 + 6) + (st - 6) * 15360 + kstep(st & 1, u) * 1024, 5120, 512, 2));
                        if (st == 6) {
                            order_post<2>(c);
                            release(c, IT_W1 + 5);
                            wait_full(c, IT_W1 + 7);
                            ga.check(c, 7);
                        }
                    }
                    wgmma_n96_acc(fa, ax, mkdesc(c.sb16, OFF_XW1 + 2048, 512, 0, 2));
                    wg_commit();
                    auto b_steps = [&](int n0, int n1) {
                        wg_fence();
#pragma unroll
                        for (int n = n0; n < n1; n++) {
                            if (n < 10) wgmma_n128_acc(fb, ga.at(6 + n / 5)[n % 5], mkdesc(c.sb16, slot_off(IT_W1 + 7) + (n / 5) * 20480 + kstep(n / 5, n % 5) * 1024, 5120, 512, 2));
                            else wgmma_n128_acc(fb, ax, mkdesc(c.sb16, OFF_XW1, 512, 0, 2));
                        }
                        wg_commit();
                    };
                    b_steps(0, 7);
                    wait_full(c, IT_W2);
                    wg_wait<1>();
                    reg_fence(fa);
                    release(c, IT_W1 + 6);
                    TL(7 + layer * 16);
#pragma unroll
                    for (int k = 0; k < 6; k++)
#pragma unroll
                        for (int i = 0; i < 4; i++) Ha[k][i] = pack2_relu(fa[8 * k + 2 * i], fa[8 * k + 2 * i + 1]);
                    publish(c, Ha, V_HA, ltag);
                    sched_fence(c);
                    b_steps(7, 11);
                    wg_wait<0>();
                    reg_fence(fb);
#pragma unroll
                    for (int k = 0; k < 8; k++)
#pragma unroll
                        for (int i = 0; i < 4; i++) Hb[k][i] = pack2_relu(fb[8 * k + 2 * i], fb[8 * k + 2 * i + 1]);
                    sched_fence(c);
                }
                float acc[80];
                uint32_t bufa[3][6][4], bufb[3][8][4];
                auto step_a = [&](int st, const uint32_t (&a)[6][4]) {
                    wg_fence();
#pragma unroll
                    for (int k = 0; k < 6; k++) {
                        const uint64_t d = mkdesc(c.sb16, slot_off(IT_W2 + st) + k * 1024, 6144, 512, 2);
                        if (st == 0 && k == 0) wgmma_n160_init(acc, a[k], d); else wgmma_n160_acc(acc, a[k], d);
                    }
                    wg_commit();
                };
                auto step_b = [&](int st, const uint32_t (&a)[8][4]) {
                    wg_fence();
#pragma unroll
                    for (int k = 0; k < 8; k++) wgmma_n160_acc(acc, a[k], mkdesc(c.sb16, slot_off(IT_W2 + st) + k * 1024, 8192, 512, 2));
                    wg_commit();
                };
                auto hprobe = [&](int vec) { if (layer == 0) probe(c, ((c.lane16() >> 3) & 6) + (r & 1), vec); };
                auto hfetch = [&](int st) {
                    if (st < 5) ld_vecs(bufa[st < 5 ? st - 2 : 0], c.box(hsrc_at(st, r)), V_HA);
                    else ld_vecs(bufb[st < 5 ? 0 : st - 5], c.box(hsrc_at(st, r)), V_HB);
                };
                auto hcheck = [&](int st) {
                    if (st < 5) check_vecs(c, bufa[st < 5 ? st - 2 : 0], ltag, [&]() { hfetch(st); });
                    else check_vecs(c, bufb[st < 5 ? 0 : st - 5], ltag, [&]() { hfetch(st); });
                };
                step_a(0, Ha);
                release(c, IT_W1 + 7);
                wait_full(c, IT_W2 + 1);
                hprobe(V_HA + 5);
                hfetch(2);
#pragma unroll
                for (int k = 0; k < 8; k++) Hb[k][0] = launder(tagged(Hb[k][0], ltag));
                auto send_b = [&](int k0, int k1) {
#pragma unroll
                    for (int k = k0; k < k1; k++) stv(c.mb + voff(V_HB + k), Hb[k][0], Hb[k][1], Hb[k][2], Hb[k][3]);
                };
                send_b(0, HB0);
                sched_fence(c);
#pragma unroll
                for (int st = 1; st < 6; st++) {
                    if (st == 1) step_b(1, Hb); else if (st < 5) step_a(st, bufa[st > 1 && st < 5 ? st - 2 : 0]); else step_b(st, bufb[0]);
                    wg_wait<1>();
                    release(c, IT_W2 + st - 1);
                    wait_full(c, IT_W2 + st + 1);
                    hcheck(st + 1);
                    if (st == 3) hprobe(V_HB + 7);
                    hfetch(st + 2);
                    if (st == 1) send_b(HB0, HB1);
                    if (st == 2) send_b(HB1, 8);
                    if (FETCH_FENCE || st == 5) sched_fence(c);
                    if (layer == 1) TL(40 + st);
                }
                order_wait<3>(c);
                wg_wait<0>();
                reg_fence(acc);
                float own[32], par[48];
                rename<48, 32>(par, acc);
                rename<32, 0>(own, acc);
#pragma unroll
                for (int st = 6; st < 8; st++) {
                    if (st == 7) { order_post<3>(c); release(c, IT_W2 + 5); wait_full(c, IT_W2 + 7); hcheck(7); order_wait<4>(c); }
                    wg_fence();
#pragma unroll
                    for (int k = 0; k < 8; k++) wgmma_n96_acc(par, bufb[st - 5][k], mkdesc(c.sb16, slot_off(IT_W2 + st) + k * 1024, 8192, 512, 2));
                    wg_commit();
                }
                order_post<4>(c);
                wait_full(c, IT_W2 + 8);
                auto own_step = [&](int i) {
                    wg_fence();
#pragma unroll
                    for (int k = 0; k < 8; k++) wgmma_n64_acc(own, bufb[1 + i][k], mkdesc(c.sb16, slot_off(IT_W2 + 8) + i * 16384 + k * 1024, 8192, 512, 2));
                    wg_commit();
                };
                own_step(0);
                wg_wait<1>();
                reg_fence(par);
                release(c, IT_W2 + 6);
                release(c, IT_W2 + 7);
                float rem[8];
                uint32_t P[5][4];
                {
                    const bool odd = r & 1;
#pragma unroll
                    for (int u = 0; u < 5; u++)
#pragma unroll
                        for (int i = 0; i < 4; i++) {
                            const int e = 8 * u + 2 * i;
                            if (u < 4) P[u][i] = pack2(par[e], par[e + 1]);
                            else P[u][i] = pack2(odd ? par[e] : par[e + 8], odd ? par[e + 1] : par[e + 9]);
                        }
                    publish(c, P, V_O, 0u);
#pragma unroll
                    for (int i = 0; i < 8; i++) rem[i] = odd ? par[40 + i] : par[32 + i];
                }
                sched_fence(c);
                own_step(1);
                if (layer == 1) TL(47);
                sched_fence(c);
                auto pfetch = [&]() { ld_vecs(P, c.box(r ^ 1), V_O); };
                if (!(LATE & 6)) pfetch();
                unpark_x(c, X);
                wg_wait<0>();
                reg_fence(own);
                release(c, IT_W2 + 8);
                if (LATE & 2) { sched_fence(c); pfetch(); }
#pragma unroll
                for (int u = 0; u < 5; u++)
#pragma unroll
                    for (int i = 0; i < 4; i++) {
                        const float rs = (i & 1) ? rsB : rsA;
                        const int e = 8 * u + 2 * i;
                        xv[e] = fmaf(rs, u < 4 ? own[e & 31] : rem[e & 7], bf_lo(X[u][i]));
                        xv[e + 1] = fmaf(rs, u < 4 ? own[(e + 1) & 31] : rem[(e + 1) & 7], bf_hi(X[u][i]));
                    }
                reg_fence(xv);
                if (layer == 0) wait_full(c, 0); else sched_fence(c);
                if (LATE & 4) pfetch();
                check_vecs(c, P, 0u, pfetch);
                TL(8 + layer * 16);
#pragma unroll
                for (int u = 0; u < 5; u++)
#pragma unroll
                    for (int i = 0; i < 4; i++) {
                        const float rs = (i & 1) ? rsB : rsA;
                        const int e = 8 * u + 2 * i;
                        xv[e] = fmaf(rs, bf_lo(P[u][i]), xv[e]);
                        xv[e + 1] = fmaf(rs, bf_hi(P[u][i]), xv[e + 1]);
                    }
                pack_x(X, xv);
                park_x(c, X);
                if (DBG_STAGE == 2 && layer == 0) store_out(c, prm.out + (size_t)(128 * blk + 32 * w + wg) * DM);
                if (layer == 1) break;
            }
            TL(9 + layer * 16);
        }
        if (DBG_STAGE == 4) store_out(c, prm.out + (size_t)(128 * blk + 32 * (warp & 3) + (warp >> 2)) * DM);
        TL(25);
        TLDUMP(64);
        if (warp == 0) reinterpret_cast<unsigned*>(prm.scr + G_EPOCH + role * 128)[c.lane()] = c.eall;
    }
}

typedef CUresult (*EncodeFn)(CUtensorMap*, CUtensorMapDataType, cuuint32_t, void*, const cuuint64_t*, const cuuint64_t*,
                             const cuuint32_t*, const cuuint32_t*, CUtensorMapInterleave, CUtensorMapSwizzle,
                             CUtensorMapL2promotion, CUtensorMapFloatOOBfill);

void encode(EncodeFn fn, CUtensorMap* tm, const void* ptr, int rank, const cuuint64_t* dims, const cuuint64_t* strides,
            const cuuint32_t* box, CUtensorMapSwizzle sw) {
    const cuuint32_t es[3] = {1, 1, 1};
    fn(tm, CU_TENSOR_MAP_DATA_TYPE_BFLOAT16, rank, const_cast<void*>(ptr), dims, strides, box, es, CU_TENSOR_MAP_INTERLEAVE_NONE, sw,
       L2PROMO, CU_TENSOR_MAP_FLOAT_OOB_FILL_NONE);
}

__global__ void occupancy_probe_kernel() {}

struct RoleMap { int v[64]; };
RoleMap make_role_map() {
    RoleMap rm;
    for (int i = 0; i < 64; i++) rm.v[i] = ((i & 7) << 3) | (i >> 3);
    cudaFuncSetAttribute(occupancy_probe_kernel, cudaFuncAttributeMaxDynamicSharedMemorySize, SMEM_BYTES);
    cudaFuncSetAttribute(occupancy_probe_kernel, cudaFuncAttributeNonPortableClusterSizeAllowed, 1);
    int N[17] = {0};
    for (int cs = 2; cs <= 16; cs++) {
        cudaLaunchConfig_t cfg = {};
        cfg.gridDim = dim3(cs * 8); cfg.blockDim = dim3(384); cfg.dynamicSmemBytes = SMEM_BYTES;
        cudaLaunchAttribute at[1];
        at[0].id = cudaLaunchAttributeClusterDimension;
        at[0].val.clusterDim.x = cs; at[0].val.clusterDim.y = 1; at[0].val.clusterDim.z = 1;
        cfg.attrs = at; cfg.numAttrs = 1;
        if (cudaOccupancyMaxActiveClusters(&N[cs], occupancy_probe_kernel, &cfg) != cudaSuccess) { cudaGetLastError(); return rm; }
    }
    int ge[10] = {0};
    for (int k = 5; k <= 8; k++) ge[k] = N[2 * k];
    ge[9] = N[9] - ge[5];
    ge[4] = N[8] - ge[8];
    ge[3] = N[6] - ge[6] - ge[9];
    ge[2] = N[4] - ge[4] - ge[6] - ge[8];
    ge[1] = ge[2];
    int total = 0;
    for (int k = 1; k <= 9; k++) { if (ge[k] < 0 || ge[k] > 16 || (k > 1 && ge[k] > ge[k - 1])) return rm; total += ge[k]; }
    const int singles = N[2] - total;
    if (singles < 0 || N[2] < 64) return rm;
    int col[64], cnt[17] = {0}, n = 0;
    for (; n < singles && n < 64; n++) col[n] = 16;
    for (int k = 1; k <= 9; k++)
        for (int j = ge[k] - 1; j >= 0 && n < 64; j--) col[n++] = (cnt[j]++ < 8) ? j : 16;
    if (n != 64) return rm;
    int pos = 0;
    for (int j = 0; j <= 16; j++)
        for (int i = 0; i < 64; i++)
            if (col[i] == j) { const int q = pos & 7; rm.v[i] = (pos & ~7) | (QUADS ? 2 * (q & 3) + (q >> 2) : q); pos++; }
    return rm;
}

}

extern "C" void kernel_launch(void* const* d_in, const int* in_sizes, int n_in, void* d_out, int out_size) {
    const __nv_bfloat16* x = (const __nv_bfloat16*)d_in[0];
    const __nv_bfloat16* wqkv = (const __nv_bfloat16*)d_in[1];
    const __nv_bfloat16* wo = (const __nv_bfloat16*)d_in[2];
    const __nv_bfloat16* w1 = (const __nv_bfloat16*)d_in[4];
    const __nv_bfloat16* w2 = (const __nv_bfloat16*)d_in[5];

    void* fnp = nullptr;
    cudaDriverEntryPointQueryResult qr;
    cudaGetDriverEntryPoint("cuTensorMapEncodeTiled", &fnp, cudaEnableDefault, &qr);
    EncodeFn fn = (EncodeFn)fnp;
    CUtensorMap tmQM, tmQR, tmWO, tmW1a, tmW1b, tmW2, tmW2a;
    {
        const cuuint64_t dims[3] = {640, 640, 3}, strides[2] = {DQKV * 2, 640 * 2};
        const cuuint64_t dims2[2] = {DQKV, 640};
        const cuuint32_t bm[2] = {64, 80}, br[3] = {16, 80, 3};
        encode(fn, &tmQM, wqkv, 2, dims2, strides, bm, CU_TENSOR_MAP_SWIZZLE_128B);
        encode(fn, &tmQR, wqkv, 3, dims, strides, br, CU_TENSOR_MAP_SWIZZLE_32B);
    }
    {
        const cuuint64_t dims[2] = {640, 640}, strides[1] = {640 * 2};
        const cuuint32_t box[2] = {32, 80};
        encode(fn, &tmWO, wo, 2, dims, strides, box, CU_TENSOR_MAP_SWIZZLE_64B);
    }
    {
        const cuuint64_t dims[3] = {32, 640, 54}, strides[2] = {DFF * 2, 64};
        const cuuint32_t boxa[3] = {32, 80, 3}, boxb[3] = {32, 80, 4};
        encode(fn, &tmW1a, w1, 3, dims, strides, boxa, CU_TENSOR_MAP_SWIZZLE_64B);
        encode(fn, &tmW1b, w1, 3, dims, strides, boxb, CU_TENSOR_MAP_SWIZZLE_64B);
    }
    {
        const cuuint64_t dims[2] = {640, DFF}, strides[1] = {640 * 2};
        const cuuint32_t box[2] = {32, 128}, boxa[2] = {32, 96};
        encode(fn, &tmW2, w2, 2, dims, strides, box, CU_TENSOR_MAP_SWIZZLE_64B);
        encode(fn, &tmW2a, w2, 2, dims, strides, boxa, CU_TENSOR_MAP_SWIZZLE_64B);
    }
    cudaFuncSetAttribute(fused_layers_kernel, cudaFuncAttributeMaxDynamicSharedMemorySize, SMEM_LAUNCH);
    const RoleMap rm = make_role_map();
    Params prm;
    void* scr = nullptr;
    cudaGetSymbolAddress(&scr, g_scratch);
    prm.scr = (char*)scr;
    prm.xin = x; prm.wqkv = wqkv; prm.w1 = w1; prm.out = (__nv_bfloat16*)d_out;
    for (int i = 0; i < 64; i++) prm.role[i] = (uint8_t)rm.v[i];
    fused_layers_kernel<<<128, 384, SMEM_LAUNCH>>>(prm, tmQM, tmQR, tmWO, tmW1a, tmW1b, tmW2, tmW2a);
}
```

```cpp
#include <cuda_runtime.h>
#include <cuda_bf16.h>
#include <cuda.h>
#include <stdint.h>

#define DBG_STAGE 4
#define TLSEL 0
#define WO_B1 2
#define WO_B2 5
#define ORDER 0x1b
#define TLW 0
#define CLR_HALO 1
#define CLR_O 0x44332
#define HB0 3
#define HB1 3

namespace {

constexpr int DM = 640, DQKV = 1920, DFF = 1728;
constexpr float LN_EPS = 1e-5f;
constexpr int SPIN_BUDGET = 1 << 20;
constexpr int REG_HELP = 56, REG_CONS = 224;

constexpr int NSLOT = 5, NITEMS_L = 30, NITEMS = 60;
constexpr int IT_WO = 9, IT_W1 = 13, IT_W2 = 21;
__host__ __device__ constexpr int slot_off(int k) { return k % 5 < 4 ? (k % 5) * 40960 : 3 * 40960 + 38912; }
constexpr int RING_BYTES = 3 * 40960 + 2 * 38912;
constexpr int STAGE_OFF = slot_off(3);

constexpr int OFF_XQM = RING_BYTES;
constexpr int OFF_XW1 = OFF_XQM + 3072;
constexpr int OFF_XQR = OFF_XW1 + 3584;
constexpr int XTRA_BYTES = 7424;
constexpr int OFF_PARK = OFF_XQM + XTRA_BYTES;
constexpr int OFF_RK = OFF_PARK + 8 * 2560;
constexpr int BAR_FULL = OFF_RK + 256, BAR_EMPTY = BAR_FULL + 40, BAR_STAGE = BAR_EMPTY + 40, BAR_CS = BAR_STAGE + 8, BAR_ORD = BAR_CS + 16;
constexpr int NORD = 5;
constexpr int BAR_X = BAR_ORD + NORD * 8;
constexpr int SMEM_BYTES = BAR_X + 16;
static_assert(SMEM_BYTES <= 232448 - 512, "smem");

constexpr int V_X = 0, V_O = 5, V_HB = 10, V_HA = 18, V_ST = 24, V_HALO = 25;
constexpr int WBOX = 5 * 512, RBOX = 8 * WBOX, PLANE = 8 * RBOX, BBOX = 9 * PLANE;
__host__ __device__ constexpr int voff(int v) { return v / 5 * PLANE + v % 5 * 512; }
constexpr uint32_t G_CS = 16 * BBOX;
constexpr uint32_t G_EPOCH = G_CS + 8 * 2 * 3 * 5120;
constexpr uint32_t G_BYTES = G_EPOCH + 128 * 128;
__device__ __align__(1024) uint4 g_scratch[G_BYTES / 16];

struct Params {
    char* scr;
    const __nv_bfloat16 *wqkv, *w1;
    uint8_t role[64];
};

#define TL(slot) do {} while (0)
#define TLH(slot) do {} while (0)
#define TLDUMP(n) do {} while (0)
#define TLINIT
constexpr int SMEM_LAUNCH = SMEM_BYTES;

template <int N> struct IntC { static constexpr int value = N; };
__device__ __forceinline__ uint32_t smem_u32(const void* p) { return (uint32_t)__cvta_generic_to_shared(p); }
__device__ __forceinline__ int launder(int v) { asm volatile("" : "+r"(v)); return v; }
__device__ __forceinline__ bool elect_one() {
    uint32_t p;
    asm volatile("{.reg .pred q; elect.sync _|q, 0xffffffff; selp.u32 %0, 1, 0, q;}" : "=r"(p));
    return p;
}
__device__ __forceinline__ void mbar_init(uint32_t b, int c) { asm volatile("mbarrier.init.shared::cta.b64 [%0], %1;" :: "r"(b), "r"(c) : "memory"); }
__device__ __forceinline__ void mbar_expect(uint32_t b, int bytes) { asm volatile("mbarrier.arrive.expect_tx.shared::cta.b64 _, [%0], %1;" :: "r"(b), "r"(bytes) : "memory"); }
__device__ __forceinline__ void mbar_arrive(uint32_t b) { asm volatile("mbarrier.arrive.shared::cta.b64 _, [%0];" :: "r"(b) : "memory"); }
__device__ __forceinline__ void mbar_arrive_cluster(uint32_t b) { asm volatile("mbarrier.arrive.shared::cluster.b64 _, [%0];" :: "r"(b) : "memory"); }
__device__ __forceinline__ void mbar_wait(uint32_t b, uint32_t parity, int& budget) {
    uint32_t ok;
#pragma unroll 1
    do {
        asm volatile("{.reg .pred p; mbarrier.try_wait.parity.shared::cta.b64 p, [%1], %2; selp.u32 %0, 1, 0, p;}" : "=r"(ok) : "r"(b), "r"(parity) : "memory");
    } while (!ok && --budget >= 0);
}
__device__ __forceinline__ void ldv(uint32_t (&v)[4], const void* p) {
    asm volatile("{.reg .b128 t; ld.relaxed.gpu.global.b128 t, [%4]; mov.b128 {%0,%1,%2,%3}, t;}"
                 : "=r"(v[0]), "=r"(v[1]), "=r"(v[2]), "=r"(v[3]) : "l"(p) : "memory");
}
__device__ __forceinline__ void stv(void* p, uint32_t a, uint32_t b, uint32_t c, uint32_t d) {
    asm volatile("{.reg .b128 t; mov.b128 t, {%0,%1,%2,%3}; st.relaxed.gpu.global.b128 [%4], t;}"
                 :: "r"(a), "r"(b), "r"(c), "r"(d), "l"(p) : "memory");
}
__device__ __forceinline__ uint32_t tagged(uint32_t w, uint32_t tag) { return (w & ~1u) | tag; }
__device__ __forceinline__ uint32_t pack2(float lo, float hi) {
    uint32_t r; asm("cvt.rn.bf16x2.f32 %0, %1, %2;" : "=r"(r) : "f"(hi), "f"(lo)); return r;
}
__device__ __forceinline__ uint32_t pack2_relu(float lo, float hi) {
    uint32_t r; asm("cvt.rn.relu.bf16x2.f32 %0, %1, %2;" : "=r"(r) : "f"(hi), "f"(lo)); return r;
}
__device__ __forceinline__ float bf_lo(uint32_t w) { return __uint_as_float(w << 16); }
__device__ __forceinline__ float bf_hi(uint32_t w) { return __uint_as_float(w & 0xffff0000u); }
__device__ __forceinline__ uint32_t movm(uint32_t a) {
    uint32_t r; asm volatile("movmatrix.sync.aligned.m8n8.trans.b16 %0, %1;" : "=r"(r) : "r"(a)); return r;
}
__device__ __forceinline__ void ldsm4(uint32_t (&v)[4], uint32_t a) {
    asm volatile("ldmatrix.sync.aligned.m8n8.x4.shared.b16 {%0,%1,%2,%3}, [%4];" : "=r"(v[0]), "=r"(v[1]), "=r"(v[2]), "=r"(v[3]) : "r"(a) : "memory");
}
__device__ __forceinline__ void ldsm4t(uint32_t (&v)[4], uint32_t a) {
    asm volatile("ldmatrix.sync.aligned.m8n8.x4.trans.shared.b16 {%0,%1,%2,%3}, [%4];" : "=r"(v[0]), "=r"(v[1]), "=r"(v[2]), "=r"(v[3]) : "r"(a) : "memory");
}
__device__ __forceinline__ void stsm4(uint32_t a, uint32_t v0, uint32_t v1, uint32_t v2, uint32_t v3) {
    asm volatile("stmatrix.sync.aligned.m8n8.x4.shared.b16 [%0], {%1,%2,%3,%4};" :: "r"(a), "r"(v0), "r"(v1), "r"(v2), "r"(v3) : "memory");
}
__device__ __forceinline__ float ex2(float x) { float r; asm("ex2.approx.ftz.f32 %0, %1;" : "=f"(r) : "f"(x)); return r; }
__device__ __forceinline__ float rcp(float x) { float r; asm("rcp.approx.ftz.f32 %0, %1;" : "=f"(r) : "f"(x)); return r; }
__device__ __forceinline__ float rsq(float x) { float r; asm("rsqrt.approx.ftz.f32 %0, %1;" : "=f"(r) : "f"(x)); return r; }
__device__ __forceinline__ void mma_k8_init(float (&d)[4], uint32_t a0, uint32_t a1, uint32_t b0) {
    asm volatile("mma.sync.aligned.m16n8k8.row.col.f32.bf16.bf16.f32 {%0,%1,%2,%3}, {%4,%5}, {%6}, {%7,%7,%7,%7};"
                 : "=f"(d[0]), "=f"(d[1]), "=f"(d[2]), "=f"(d[3]) : "r"(a0), "r"(a1), "r"(b0), "f"(0.f));
}
__device__ __forceinline__ void mma_k16_acc(float (&d)[4], uint32_t a0, uint32_t a1, uint32_t a2, uint32_t a3, uint32_t b0, uint32_t b1) {
    asm volatile("mma.sync.aligned.m16n8k16.row.col.f32.bf16.bf16.f32 {%0,%1,%2,%3}, {%4,%5,%6,%7}, {%8,%9}, {%0,%1,%2,%3};"
                 : "+f"(d[0]), "+f"(d[1]), "+f"(d[2]), "+f"(d[3]) : "r"(a0), "r"(a1), "r"(a2), "r"(a3), "r"(b0), "r"(b1));
}
__device__ __forceinline__ void wg_fence() { asm volatile("wgmma.fence.sync.aligned;" ::: "memory"); }
__device__ __forceinline__ void wg_commit() { asm volatile("wgmma.commit_group.sync.aligned;" ::: "memory"); }
template <int N> __device__ __forceinline__ void wg_wait() { asm volatile("wgmma.wait_group.sync.aligned %0;" :: "n"(N) : "memory"); }
template <int N> __device__ __forceinline__ void reg_fence(float (&d)[N]) {
#pragma unroll
    for (int i = 0; i < N; i++) asm volatile("" : "+f"(d[i]) :: "memory");
}
template <int N, int OFF, int TOT> __device__ __forceinline__ void rename(float (&d)[N], const float (&s)[TOT]) {
#pragma unroll
    for (int i = 0; i < N; i++) asm volatile("mov.f32 %0, %1;" : "=f"(d[i]) : "f"(s[OFF + i]));
}
__device__ __forceinline__ uint64_t mkdesc(uint32_t a16, uint32_t off, uint32_t lbo, uint32_t sbo, int sw) {
    const uint32_t lo = a16 + ((off >> 4) + ((lbo >> 4) << 16));
    const uint32_t hi = (sbo >> 4) | ((uint32_t)sw << 30);
    return ((uint64_t)hi << 32) | lo;
}
__device__ __forceinline__ void tma2d_mc(uint32_t dst, const CUtensorMap* tm, int c0, int c1, uint32_t bar) {
    asm volatile("cp.async.bulk.tensor.2d.shared::cluster.global.mbarrier::complete_tx::bytes.multicast::cluster [%0], [%1, {%3, %4}], [%2], %5;"
                 :: "r"(dst), "l"(tm), "r"(bar), "r"(c0), "r"(c1), "h"((uint16_t)3) : "memory");
}
__device__ __forceinline__ void tma2d(uint32_t dst, const CUtensorMap* tm, int c0, int c1, uint32_t bar) {
    asm volatile("cp.async.bulk.tensor.2d.shared::cluster.global.mbarrier::complete_tx::bytes [%0], [%1, {%3, %4}], [%2];"
                 :: "r"(dst), "l"(tm), "r"(bar), "r"(c0), "r"(c1) : "memory");
}
__device__ __forceinline__ void tma3d_mc(uint32_t dst, const CUtensorMap* tm, int c0, int c1, int c2, uint32_t bar) {
    asm volatile("cp.async.bulk.tensor.3d.shared::cluster.global.mbarrier::complete_tx::bytes.multicast::cluster [%0], [%1, {%3, %4, %5}], [%2], %6;"
                 :: "r"(dst), "l"(tm), "r"(bar), "r"(c0), "r"(c1), "r"(c2), "h"((uint16_t)3) : "memory");
}
__device__ __forceinline__ void prefetch_map(const CUtensorMap* tm) { asm volatile("prefetch.tensormap [%0];" :: "l"(tm) : "memory"); }

__device__ __forceinline__ void wgmma_n192_acc(float (&d)[96], const uint32_t (&a)[4], uint64_t db) {
    asm volatile("{.reg .pred p; setp.eq.b32 p, 0, 0;\n"
        "wgmma.mma_async.sync.aligned.m64n192k16.f32.bf16.bf16 {"
        "%0, %1, %2, %3, %4, %5, %6, %7, %8, %9, %10, %11, %12, %13, %14, %15, %16, %17, %18, %19, %20, %21, %22, %23, "
        "%24, %25, %26, %27, %28, %29, %30, %31, %32, %33, %34, %35, %36, %37, %38, %39, %40, %41, %42, %43, %44, %45, %46, %47, "
        "%48, %49, %50, %51, %52, %53, %54, %55, %56, %57, %58, %59, %60, %61, %62, %63, %64, %65, %66, %67, %68, %69, %70, %71, "
        "%72, %73, %74, %75, %76, %77, %78, %79, %80, %81, %82, %83, %84, %85, %86, %87, %88, %89, %90, %91, %92, %93, %94, %95"
        "}, {%96, %97, %98, %99}, %100, p, 1, 1, 1;}\n"
        : "+f"(d[0]), "+f"(d[1]), "+f"(d[2]), "+f"(d[3]), "+f"(d[4]), "+f"(d[5]), "+f"(d[6]), "+f"(d[7]), "+f"(d[8]), "+f"(d[9]), "+f"(d[10]), "+f"(d[11]),
          "+f"(d[12]), "+f"(d[13]), "+f"(d[14]), "+f"(d[15]), "+f"(d[16]), "+f"(d[17]), "+f"(d[18]), "+f"(d[19]), "+f"(d[20]), "+f"(d[21]), "+f"(d[22]), "+f"(d[23]),
          "+f"(d[24]), "+f"(d[25]), "+f"(d[26]), "+f"(d[27]), "+f"(d[28]), "+f"(d[29]), "+f"(d[30]), "+f"(d[31]), "+f"(d[32]), "+f"(d[33]), "+f"(d[34]), "+f"(d[35]),
          "+f"(d[36]), "+f"(d[37]), "+f"(d[38]), "+f"(d[39]), "+f"(d[40]), "+f"(d[41]), "+f"(d[42]), "+f"(d[43]), "+f"(d[44]), "+f"(d[45]), "+f"(d[46]), "+f"(d[47]),
          "+f"(d[48]), "+f"(d[49]), "+f"(d[50]), "+f"(d[51]), "+f"(d[52]), "+f"(d[53]), "+f"(d[54]), "+f"(d[55]), "+f"(d[56]), "+f"(d[57]), "+f"(d[58]), "+f"(d[59]),
          "+f"(d[60]), "+f"(d[61]), "+f"(d[62]), "+f"(d[63]), "+f"(d[64]), "+f"(d[65]), "+f"(d[66]), "+f"(d[67]), "+f"(d[68]), "+f"(d[69]), "+f"(d[70]), "+f"(d[71]),
          "+f"(d[72]), "+f"(d[73]), "+f"(d[74]), "+f"(d[75]), "+f"(d[76]), "+f"(d[77]), "+f"(d[78]), "+f"(d[79]), "+f"(d[80]), "+f"(d[81]), "+f"(d[82]), "+f"(d[83]),
          "+f"(d[84]), "+f"(d[85]), "+f"(d[86]), "+f"(d[87]), "+f"(d[88]), "+f"(d[89]), "+f"(d[90]), "+f"(d[91]), "+f"(d[92]), "+f"(d[93]), "+f"(d[94]), "+f"(d[95])
        : "r"(a[0]), "r"(a[1]), "r"(a[2]), "r"(a[3]), "l"(db));
}
__device__ __forceinline__ void wgmma_n192_init(float (&d)[96], const uint32_t (&a)[4], uint64_t db) {
    asm volatile("{.reg .pred p; setp.ne.b32 p, 0, 0;\n"
        "wgmma.mma_async.sync.aligned.m64n192k16.f32.bf16.bf16 {"
        "%0, %1, %2, %3, %4, %5, %6, %7, %8, %9, %10, %11, %12, %13, %14, %15, %16, %17, %18, %19, %20, %21, %22, %23, "
        "%24, %25, %26, %27, %28, %29, %30, %31, %32, %33, %34, %35, %36, %37, %38, %39, %40, %41, %42, %43, %44, %45, %46, %47, "
        "%48, %49, %50, %51, %52, %53, %54, %55, %56, %57, %58, %59, %60, %61, %62, %63, %64, %65, %66, %67, %68, %69, %70, %71, "
        "%72, %73, %74, %75, %76, %77, %78, %79, %80, %81, %82, %83, %84, %85, %86, %87, %88, %89, %90, %91, %92, %93, %94, %95"
        "}, {%96, %97, %98, %99}, %100, p, 1, 1, 1;}\n"
        : "=f"(d[0]), "=f"(d[1]), "=f"(d[2]), "=f"(d[3]), "=f"(d[4]), "=f"(d[5]), "=f"(d[6]), "=f"(d[7]), "=f"(d[8]), "=f"(d[9]), "=f"(d[10]), "=f"(d[11]),
          "=f"(d[12]), "=f"(d[13]), "=f"(d[14]), "=f"(d[15]), "=f"(d[16]), "=f"(d[17]), "=f"(d[18]), "=f"(d[19]), "=f"(d[20]), "=f"(d[21]), "=f"(d[22]), "=f"(d[23]),
          "=f"(d[24]), "=f"(d[25]), "=f"(d[26]), "=f"(d[27]), "=f"(d[28]), "=f"(d[29]), "=f"(d[30]), "=f"(d[31]), "=f"(d[32]), "=f"(d[33]), "=f"(d[34]), "=f"(d[35]),
          "=f"(d[36]), "=f"(d[37]), "=f"(d[38]), "=f"(d[39]), "=f"(d[40]), "=f"(d[41]), "=f"(d[42]), "=f"(d[43]), "=f"(d[44]), "=f"(d[45]), "=f"(d[46]), "=f"(d[47]),
          "=f"(d[48]), "=f"(d[49]), "=f"(d[50]), "=f"(d[51]), "=f"(d[52]), "=f"(d[53]), "=f"(d[54]), "=f"(d[55]), "=f"(d[56]), "=f"(d[57]), "=f"(d[58]), "=f"(d[59]),
          "=f"(d[60]), "=f"(d[61]), "=f"(d[62]), "=f"(d[63]), "=f"(d[64]), "=f"(d[65]), "=f"(d[66]), "=f"(d[67]), "=f"(d[68]), "=f"(d[69]), "=f"(d[70]), "=f"(d[71]),
          "=f"(d[72]), "=f"(d[73]), "=f"(d[74]), "=f"(d[75]), "=f"(d[76]), "=f"(d[77]), "=f"(d[78]), "=f"(d[79]), "=f"(d[80]), "=f"(d[81]), "=f"(d[82]), "=f"(d[83]),
          "=f"(d[84]), "=f"(d[85]), "=f"(d[86]), "=f"(d[87]), "=f"(d[88]), "=f"(d[89]), "=f"(d[90]), "=f"(d[91]), "=f"(d[92]), "=f"(d[93]), "=f"(d[94]), "=f"(d[95])
        : "r"(a[0]), "r"(a[1]), "r"(a[2]), "r"(a[3]), "l"(db));
}
__device__ __forceinline__ void wgmma_n48_acc(float (&d)[24], const uint32_t (&a)[4], uint64_t db) {
    asm volatile("{.reg .pred p; setp.eq.b32 p, 0, 0;\n"
        "wgmma.mma_async.sync.aligned.m64n48k16.f32.bf16.bf16 {"
        "%0, %1, %2, %3, %4, %5, %6, %7, %8, %9, %10, %11, %12, %13, %14, %15, %16, %17, %18, %19, %20, %21, %22, %23"
        "}, {%24, %25, %26, %27}, %28, p, 1, 1, 1;}\n"
        : "+f"(d[0]), "+f"(d[1]), "+f"(d[2]), "+f"(d[3]), "+f"(d[4]), "+f"(d[5]), "+f"(d[6]), "+f"(d[7]), "+f"(d[8]), "+f"(d[9]), "+f"(d[10]), "+f"(d[11]),
          "+f"(d[12]), "+f"(d[13]), "+f"(d[14]), "+f"(d[15]), "+f"(d[16]), "+f"(d[17]), "+f"(d[18]), "+f"(d[19]), "+f"(d[20]), "+f"(d[21]), "+f"(d[22]), "+f"(d[23])
        : "r"(a[0]), "r"(a[1]), "r"(a[2]), "r"(a[3]), "l"(db));
}
__device__ __forceinline__ void wgmma_n48_init(float (&d)[24], const uint32_t (&a)[4], uint64_t db) {
    asm volatile("{.reg .pred p; setp.ne.b32 p, 0, 0;\n"
        "wgmma.mma_async.sync.aligned.m64n48k16.f32.bf16.bf16 {"
        "%0, %1, %2, %3, %4, %5, %6, %7, %8, %9, %10, %11, %12, %13, %14, %15, %16, %17, %18, %19, %20, %21, %22, %23"
        "}, {%24, %25, %26, %27}, %28, p, 1, 1, 1;}\n"
        : "=f"(d[0]), "=f"(d[1]), "=f"(d[2]), "=f"(d[3]), "=f"(d[4]), "=f"(d[5]), "=f"(d[6]), "=f"(d[7]), "=f"(d[8]), "=f"(d[9]), "=f"(d[10]), "=f"(d[11]),
          "=f"(d[12]), "=f"(d[13]), "=f"(d[14]), "=f"(d[15]), "=f"(d[16]), "=f"(d[17]), "=f"(d[18]), "=f"(d[19]), "=f"(d[20]), "=f"(d[21]), "=f"(d[22]), "=f"(d[23])
        : "r"(a[0]), "r"(a[1]), "r"(a[2]), "r"(a[3]), "l"(db));
}
__device__ __forceinline__ void wgmma_n224_acc(float (&d)[112], const uint32_t (&a)[4], uint64_t db) {
    asm volatile("{.reg .pred p; setp.eq.b32 p, 0, 0;\n"
        "wgmma.mma_async.sync.aligned.m64n224k16.f32.bf16.bf16 {"
        "%0, %1, %2, %3, %4, %5, %6, %7, %8, %9, %10, %11, %12, %13, %14, %15, %16, %17, %18, %19, %20, %21, %22, %23, "
        "%24, %25, %26, %27, %28, %29, %30, %31, %32, %33, %34, %35, %36, %37, %38, %39, %40, %41, %42, %43, %44, %45, %46, %47, "
        "%48, %49, %50, %51, %52, %53, %54, %55, %56, %57, %58, %59, %60, %61, %62, %63, %64, %65, %66, %67, %68, %69, %70, %71, "
        "%72, %73, %74, %75, %76, %77, %78, %79, %80, %81, %82, %83, %84, %85, %86, %87, %88, %89, %90, %91, %92, %93, %94, %95, "
        "%96, %97, %98, %99, %100, %101, %102, %103, %104, %105, %106, %107, %108, %109, %110, %111"
        "}, {%112, %113, %114, %115}, %116, p, 1, 1, 1;}\n"
        : "+f"(d[0]), "+f"(d[1]), "+f"(d[2]), "+f"(d[3]), "+f"(d[4]), "+f"(d[5]), "+f"(d[6]), "+f"(d[7]), "+f"(d[8]), "+f"(d[9]), "+f"(d[10]), "+f"(d[11]),
          "+f"(d[12]), "+f"(d[13]), "+f"(d[14]), "+f"(d[15]), "+f"(d[16]), "+f"(d[17]), "+f"(d[18]), "+f"(d[19]), "+f"(d[20]), "+f"(d[21]), "+f"(d[22]), "+f"(d[23]),
          "+f"(d[24]), "+f"(d[25]), "+f"(d[26]), "+f"(d[27]), "+f"(d[28]), "+f"(d[29]), "+f"(d[30]), "+f"(d[31]), "+f"(d[32]), "+f"(d[33]), "+f"(d[34]), "+f"(d[35]),
          "+f"(d[36]), "+f"(d[37]), "+f"(d[38]), "+f"(d[39]), "+f"(d[40]), "+f"(d[41]), "+f"(d[42]), "+f"(d[43]), "+f"(d[44]), "+f"(d[45]), "+f"(d[46]), "+f"(d[47]),
          "+f"(d[48]), "+f"(d[49]), "+f"(d[50]), "+f"(d[51]), "+f"(d[52]), "+f"(d[53]), "+f"(d[54]), "+f"(d[55]), "+f"(d[56]), "+f"(d[57]), "+f"(d[58]), "+f"(d[59]),
          "+f"(d[60]), "+f"(d[61]), "+f"(d[62]), "+f"(d[63]), "+f"(d[64]), "+f"(d[65]), "+f"(d[66]), "+f"(d[67]), "+f"(d[68]), "+f"(d[69]), "+f"(d[70]), "+f"(d[71]),
          "+f"(d[72]), "+f"(d[73]), "+f"(d[74]), "+f"(d[75]), "+f"(d[76]), "+f"(d[77]), "+f"(d[78]), "+f"(d[79]), "+f"(d[80]), "+f"(d[81]), "+f"(d[82]), "+f"(d[83]),
          "+f"(d[84]), "+f"(d[85]), "+f"(d[86]), "+f"(d[87]), "+f"(d[88]), "+f"(d[89]), "+f"(d[90]), "+f"(d[91]), "+f"(d[92]), "+f"(d[93]), "+f"(d[94]), "+f"(d[95]),
          "+f"(d[96]), "+f"(d[97]), "+f"(d[98]), "+f"(d[99]), "+f"(d[100]), "+f"(d[101]), "+f"(d[102]), "+f"(d[103]), "+f"(d[104]), "+f"(d[105]), "+f"(d[106]), "+f"(d[107]),
          "+f"(d[108]), "+f"(d[109]), "+f"(d[110]), "+f"(d[111])
        : "r"(a[0]), "r"(a[1]), "r"(a[2]), "r"(a[3]), "l"(db));
}
__device__ __forceinline__ void wgmma_n224_init(float (&d)[112], const uint32_t (&a)[4], uint64_t db) {
    asm volatile("{.reg .pred p; setp.ne.b32 p, 0, 0;\n"
        "wgmma.mma_async.sync.aligned.m64n224k16.f32.bf16.bf16 {"
        "%0, %1, %2, %3, %4, %5, %6, %7, %8, %9, %10, %11, %12, %13, %14, %15, %16, %17, %18, %19, %20, %21, %22, %23, "
        "%24, %25, %26, %27, %28, %29, %30, %31, %32, %33, %34, %35, %36, %37, %38, %39, %40, %41, %42, %43, %44, %45, %46, %47, "
        "%48, %49, %50, %51, %52, %53, %54, %55, %56, %57, %58, %59, %60, %61, %62, %63, %64, %65, %66, %67, %68, %69, %70, %71, "
        "%72, %73, %74, %75, %76, %77, %78, %79, %80, %81, %82, %83, %84, %85, %86, %87, %88, %89, %90, %91, %92, %93, %94, %95, "
        "%96, %97, %98, %99, %100, %101, %102, %103, %104, %105, %106, %107, %108, %109, %110, %111"
        "}, {%112, %113, %114, %115}, %116, p, 1, 1, 1;}\n"
        : "=f"(d[0]), "=f"(d[1]), "=f"(d[2]), "=f"(d[3]), "=f"(d[4]), "=f"(d[5]), "=f"(d[6]), "=f"(d[7]), "=f"(d[8]), "=f"(d[9]), "=f"(d[10]), "=f"(d[11]),
          "=f"(d[12]), "=f"(d[13]), "=f"(d[14]), "=f"(d[15]), "=f"(d[16]), "=f"(d[17]), "=f"(d[18]), "=f"(d[19]), "=f"(d[20]), "=f"(d[21]), "=f"(d[22]), "=f"(d[23]),
          "=f"(d[24]), "=f"(d[25]), "=f"(d[26]), "=f"(d[27]), "=f"(d[28]), "=f"(d[29]), "=f"(d[30]), "=f"(d[31]), "=f"(d[32]), "=f"(d[33]), "=f"(d[34]), "=f"(d[35]),
          "=f"(d[36]), "=f"(d[37]), "=f"(d[38]), "=f"(d[39]), "=f"(d[40]), "=f"(d[41]), "=f"(d[42]), "=f"(d[43]), "=f"(d[44]), "=f"(d[45]), "=f"(d[46]), "=f"(d[47]),
          "=f"(d[48]), "=f"(d[49]), "=f"(d[50]), "=f"(d[51]), "=f"(d[52]), "=f"(d[53]), "=f"(d[54]), "=f"(d[55]), "=f"(d[56]), "=f"(d[57]), "=f"(d[58]), "=f"(d[59]),
          "=f"(d[60]), "=f"(d[61]), "=f"(d[62]), "=f"(d[63]), "=f"(d[64]), "=f"(d[65]), "=f"(d[66]), "=f"(d[67]), "=f"(d[68]), "=f"(d[69]), "=f"(d[70]), "=f"(d[71]),
          "=f"(d[72]), "=f"(d[73]), "=f"(d[74]), "=f"(d[75]), "=f"(d[76]), "=f"(d[77]), "=f"(d[78]), "=f"(d[79]), "=f"(d[80]), "=f"(d[81]), "=f"(d[82]), "=f"(d[83]),
          "=f"(d[84]), "=f"(d[85]), "=f"(d[86]), "=f"(d[87]), "=f"(d[88]), "=f"(d[89]), "=f"(d[90]), "=f"(d[91]), "=f"(d[92]), "=f"(d[93]), "=f"(d[94]), "=f"(d[95]),
          "=f"(d[96]), "=f"(d[97]), "=f"(d[98]), "=f"(d[99]), "=f"(d[100]), "=f"(d[101]), "=f"(d[102]), "=f"(d[103]), "=f"(d[104]), "=f"(d[105]), "=f"(d[106]), "=f"(d[107]),
          "=f"(d[108]), "=f"(d[109]), "=f"(d[110]), "=f"(d[111])
        : "r"(a[0]), "r"(a[1]), "r"(a[2]), "r"(a[3]), "l"(db));
}
__device__ __forceinline__ void wgmma_n80_acc(float (&d)[40], const uint32_t (&a)[4], uint64_t db) {
    asm volatile("{.reg .pred p; setp.eq.b32 p, 0, 0;\n"
        "wgmma.mma_async.sync.aligned.m64n80k16.f32.bf16.bf16 {"
        "%0, %1, %2, %3, %4, %5, %6, %7, %8, %9, %10, %11, %12, %13, %14, %15, %16, %17, %18, %19, %20, %21, %22, %23, "
        "%24, %25, %26, %27, %28, %29, %30, %31, %32, %33, %34, %35, %36, %37, %38, %39"
        "}, {%40, %41, %42, %43}, %44, p, 1, 1, 1;}\n"
        : "+f"(d[0]), "+f"(d[1]), "+f"(d[2]), "+f"(d[3]), "+f"(d[4]), "+f"(d[5]), "+f"(d[6]), "+f"(d[7]), "+f"(d[8]), "+f"(d[9]), "+f"(d[10]), "+f"(d[11]),
          "+f"(d[12]), "+f"(d[13]), "+f"(d[14]), "+f"(d[15]), "+f"(d[16]), "+f"(d[17]), "+f"(d[18]), "+f"(d[19]), "+f"(d[20]), "+f"(d[21]), "+f"(d[22]), "+f"(d[23]),
          "+f"(d[24]), "+f"(d[25]), "+f"(d[26]), "+f"(d[27]), "+f"(d[28]), "+f"(d[29]), "+f"(d[30]), "+f"(d[31]), "+f"(d[32]), "+f"(d[33]), "+f"(d[34]), "+f"(d[35]),
          "+f"(d[36]), "+f"(d[37]), "+f"(d[38]), "+f"(d[39])
        : "r"(a[0]), "r"(a[1]), "r"(a[2]), "r"(a[3]), "l"(db));
}
__device__ __forceinline__ void wgmma_n160_acc(float (&d)[80], const uint32_t (&a)[4], uint64_t db) {
    asm volatile("{.reg .pred p; setp.eq.b32 p, 0, 0;\n"
        "wgmma.mma_async.sync.aligned.m64n160k16.f32.bf16.bf16 {"
        "%0, %1, %2, %3, %4, %5, %6, %7, %8, %9, %10, %11, %12, %13, %14, %15, %16, %17, %18, %19, %20, %21, %22, %23, "
        "%24, %25, %26, %27, %28, %29, %30, %31, %32, %33, %34, %35, %36, %37, %38, %39, %40, %41, %42, %43, %44, %45, %46, %47, "
        "%48, %49, %50, %51, %52, %53, %54, %55, %56, %57, %58, %59, %60, %61, %62, %63, %64, %65, %66, %67, %68, %69, %70, %71, "
        "%72, %73, %74, %75, %76, %77, %78, %79"
        "}, {%80, %81, %82, %83}, %84, p, 1, 1, 1;}\n"
        : "+f"(d[0]), "+f"(d[1]), "+f"(d[2]), "+f"(d[3]), "+f"(d[4]), "+f"(d[5]), "+f"(d[6]), "+f"(d[7]), "+f"(d[8]), "+f"(d[9]), "+f"(d[10]), "+f"(d[11]),
          "+f"(d[12]), "+f"(d[13]), "+f"(d[14]), "+f"(d[15]), "+f"(d[16]), "+f"(d[17]), "+f"(d[18]), "+f"(d[19]), "+f"(d[20]), "+f"(d[21]), "+f"(d[22]), "+f"(d[23]),
          "+f"(d[24]), "+f"(d[25]), "+f"(d[26]), "+f"(d[27]), "+f"(d[28]), "+f"(d[29]), "+f"(d[30]), "+f"(d[31]), "+f"(d[32]), "+f"(d[33]), "+f"(d[34]), "+f"(d[35]),
          "+f"(d[36]), "+f"(d[37]), "+f"(d[38]), "+f"(d[39]), "+f"(d[40]), "+f"(d[41]), "+f"(d[42]), "+f"(d[43]), "+f"(d[44]), "+f"(d[45]), "+f"(d[46]), "+f"(d[47]),
          "+f"(d[48]), "+f"(d[49]), "+f"(d[50]), "+f"(d[51]), "+f"(d[52]), "+f"(d[53]), "+f"(d[54]), "+f"(d[55]), "+f"(d[56]), "+f"(d[57]), "+f"(d[58]), "+f"(d[59]),
          "+f"(d[60]), "+f"(d[61]), "+f"(d[62]), "+f"(d[63]), "+f"(d[64]), "+f"(d[65]), "+f"(d[66]), "+f"(d[67]), "+f"(d[68]), "+f"(d[69]), "+f"(d[70]), "+f"(d[71]),
          "+f"(d[72]), "+f"(d[73]), "+f"(d[74]), "+f"(d[75]), "+f"(d[76]), "+f"(d[77]), "+f"(d[78]), "+f"(d[79])
        : "r"(a[0]), "r"(a[1]), "r"(a[2]), "r"(a[3]), "l"(db));
}
__device__ __forceinline__ void wgmma_n160_init(float (&d)[80], const uint32_t (&a)[4], uint64_t db) {
    asm volatile("{.reg .pred p; setp.ne.b32 p, 0, 0;\n"
        "wgmma.mma_async.sync.aligned.m64n160k16.f32.bf16.bf16 {"
        "%0, %1, %2, %3, %4, %5, %6, %7, %8, %9, %10, %11, %12, %13, %14, %15, %16, %17, %18, %19, %20, %21, %22, %23, "
        "%24, %25, %26, %27, %28, %29, %30, %31, %32, %33, %34, %35, %36, %37, %38, %39, %40, %41, %42, %43, %44, %45, %46, %47, "
        "%48, %49, %50, %51, %52, %53, %54, %55, %56, %57, %58, %59, %60, %61, %62, %63, %64, %65, %66, %67, %68, %69, %70, %71, "
        "%72, %73, %74, %75, %76, %77, %78, %79"
        "}, {%80, %81, %82, %83}, %84, p, 1, 1, 1;}\n"
        : "=f"(d[0]), "=f"(d[1]), "=f"(d[2]), "=f"(d[3]), "=f"(d[4]), "=f"(d[5]), "=f"(d[6]), "=f"(d[7]), "=f"(d[8]), "=f"(d[9]), "=f"(d[10]), "=f"(d[11]),
          "=f"(d[12]), "=f"(d[13]), "=f"(d[14]), "=f"(d[15]), "=f"(d[16]), "=f"(d[17]), "=f"(d[18]), "=f"(d[19]), "=f"(d[20]), "=f"(d[21]), "=f"(d[22]), "=f"(d[23]),
          "=f"(d[24]), "=f"(d[25]), "=f"(d[26]), "=f"(d[27]), "=f"(d[28]), "=f"(d[29]), "=f"(d[30]), "=f"(d[31]), "=f"(d[32]), "=f"(d[33]), "=f"(d[34]), "=f"(d[35]),
          "=f"(d[36]), "=f"(d[37]), "=f"(d[38]), "=f"(d[39]), "=f"(d[40]), "=f"(d[41]), "=f"(d[42]), "=f"(d[43]), "=f"(d[44]), "=f"(d[45]), "=f"(d[46]), "=f"(d[47]),
          "=f"(d[48]), "=f"(d[49]), "=f"(d[50]), "=f"(d[51]), "=f"(d[52]), "=f"(d[53]), "=f"(d[54]), "=f"(d[55]), "=f"(d[56]), "=f"(d[57]), "=f"(d[58]), "=f"(d[59]),
          "=f"(d[60]), "=f"(d[61]), "=f"(d[62]), "=f"(d[63]), "=f"(d[64]), "=f"(d[65]), "=f"(d[66]), "=f"(d[67]), "=f"(d[68]), "=f"(d[69]), "=f"(d[70]), "=f"(d[71]),
          "=f"(d[72]), "=f"(d[73]), "=f"(d[74]), "=f"(d[75]), "=f"(d[76]), "=f"(d[77]), "=f"(d[78]), "=f"(d[79])
        : "r"(a[0]), "r"(a[1]), "r"(a[2]), "r"(a[3]), "l"(db));
}
__device__ __forceinline__ void wgmma_n128_acc(float (&d)[64], const uint32_t (&a)[4], uint64_t db) {
    asm volatile("{.reg .pred p; setp.eq.b32 p, 0, 0;\n"
        "wgmma.mma_async.sync.aligned.m64n128k16.f32.bf16.bf16 {"
        "%0, %1, %2, %3, %4, %5, %6, %7, %8, %9, %10, %11, %12, %13, %14, %15, %16, %17, %18, %19, %20, %21, %22, %23, "
        "%24, %25, %26, %27, %28, %29, %30, %31, %32, %33, %34, %35, %36, %37, %38, %39, %40, %41, %42, %43, %44, %45, %46, %47, "
        "%48, %49, %50, %51, %52, %53, %54, %55, %56, %57, %58, %59, %60, %61, %62, %63"
        "}, {%64, %65, %66, %67}, %68, p, 1, 1, 1;}\n"
        : "+f"(d[0]), "+f"(d[1]), "+f"(d[2]), "+f"(d[3]), "+f"(d[4]), "+f"(d[5]), "+f"(d[6]), "+f"(d[7]), "+f"(d[8]), "+f"(d[9]), "+f"(d[10]), "+f"(d[11]),
          "+f"(d[12]), "+f"(d[13]), "+f"(d[14]), "+f"(d[15]), "+f"(d[16]), "+f"(d[17]), "+f"(d[18]), "+f"(d[19]), "+f"(d[20]), "+f"(d[21]), "+f"(d[22]), "+f"(d[23]),
          "+f"(d[24]), "+f"(d[25]), "+f"(d[26]), "+f"(d[27]), "+f"(d[28]), "+f"(d[29]), "+f"(d[30]), "+f"(d[31]), "+f"(d[32]), "+f"(d[33]), "+f"(d[34]), "+f"(d[35]),
          "+f"(d[36]), "+f"(d[37]), "+f"(d[38]), "+f"(d[39]), "+f"(d[40]), "+f"(d[41]), "+f"(d[42]), "+f"(d[43]), "+f"(d[44]), "+f"(d[45]), "+f"(d[46]), "+f"(d[47]),
          "+f"(d[48]), "+f"(d[49]), "+f"(d[50]), "+f"(d[51]), "+f"(d[52]), "+f"(d[53]), "+f"(d[54]), "+f"(d[55]), "+f"(d[56]), "+f"(d[57]), "+f"(d[58]), "+f"(d[59]),
          "+f"(d[60]), "+f"(d[61]), "+f"(d[62]), "+f"(d[63])
        : "r"(a[0]), "r"(a[1]), "r"(a[2]), "r"(a[3]), "l"(db));
}
__device__ __forceinline__ void wgmma_n96_acc(float (&d)[48], const uint32_t (&a)[4], uint64_t db) {
    asm volatile("{.reg .pred p; setp.eq.b32 p, 0, 0;\n"
        "wgmma.mma_async.sync.aligned.m64n96k16.f32.bf16.bf16 {"
        "%0, %1, %2, %3, %4, %5, %6, %7, %8, %9, %10, %11, %12, %13, %14, %15, %16, %17, %18, %19, %20, %21, %22, %23, "
        "%24, %25, %26, %27, %28, %29, %30, %31, %32, %33, %34, %35, %36, %37, %38, %39, %40, %41, %42, %43, %44, %45, %46, %47"
        "}, {%48, %49, %50, %51}, %52, p, 1, 1, 1;}\n"
        : "+f"(d[0]), "+f"(d[1]), "+f"(d[2]), "+f"(d[3]), "+f"(d[4]), "+f"(d[5]), "+f"(d[6]), "+f"(d[7]), "+f"(d[8]), "+f"(d[9]), "+f"(d[10]), "+f"(d[11]),
          "+f"(d[12]), "+f"(d[13]), "+f"(d[14]), "+f"(d[15]), "+f"(d[16]), "+f"(d[17]), "+f"(d[18]), "+f"(d[19]), "+f"(d[20]), "+f"(d[21]), "+f"(d[22]), "+f"(d[23]),
          "+f"(d[24]), "+f"(d[25]), "+f"(d[26]), "+f"(d[27]), "+f"(d[28]), "+f"(d[29]), "+f"(d[30]), "+f"(d[31]), "+f"(d[32]), "+f"(d[33]), "+f"(d[34]), "+f"(d[35]),
          "+f"(d[36]), "+f"(d[37]), "+f"(d[38]), "+f"(d[39]), "+f"(d[40]), "+f"(d[41]), "+f"(d[42]), "+f"(d[43]), "+f"(d[44]), "+f"(d[45]), "+f"(d[46]), "+f"(d[47])
        : "r"(a[0]), "r"(a[1]), "r"(a[2]), "r"(a[3]), "l"(db));
}
__device__ __forceinline__ void wgmma_n64_acc(float (&d)[32], const uint32_t (&a)[4], uint64_t db) {
    asm volatile("{.reg .pred p; setp.eq.b32 p, 0, 0;\n"
        "wgmma.mma_async.sync.aligned.m64n64k16.f32.bf16.bf16 {"
        "%0, %1, %2, %3, %4, %5, %6, %7, %8, %9, %10, %11, %12, %13, %14, %15, %16, %17, %18, %19, %20, %21, %22, %23, "
        "%24, %25, %26, %27, %28, %29, %30, %31"
        "}, {%32, %33, %34, %35}, %36, p, 1, 1, 1;}\n"
        : "+f"(d[0]), "+f"(d[1]), "+f"(d[2]), "+f"(d[3]), "+f"(d[4]), "+f"(d[5]), "+f"(d[6]), "+f"(d[7]), "+f"(d[8]), "+f"(d[9]), "+f"(d[10]), "+f"(d[11]),
          "+f"(d[12]), "+f"(d[13]), "+f"(d[14]), "+f"(d[15]), "+f"(d[16]), "+f"(d[17]), "+f"(d[18]), "+f"(d[19]), "+f"(d[20]), "+f"(d[21]), "+f"(d[22]), "+f"(d[23]),
          "+f"(d[24]), "+f"(d[25]), "+f"(d[26]), "+f"(d[27]), "+f"(d[28]), "+f"(d[29]), "+f"(d[30]), "+f"(d[31])
        : "r"(a[0]), "r"(a[1]), "r"(a[2]), "r"(a[3]), "l"(db));
}

__device__ __forceinline__ int slice_at(int t, int r) { return t < 2 ? r ^ t : (t - 2) + ((t - 2) >= (r & 6) ? 2 : 0); }
__device__ __forceinline__ int main_col(int j) { return 80 * j + 16 * (j & 1); }
__device__ __forceinline__ int rem_col(int j) { return 80 * j + 64 - 64 * (j & 1); }
__device__ __forceinline__ int kstep(int odd, int u) { return u < 4 ? odd + u : 4 - 4 * odd; }
__device__ __forceinline__ int hsrc_at(int t, int r) {
    if (t < 2) return r;
    const int i = t < 5 ? t - 2 : t - 5;
    return 2 * (i + (i >= (r >> 1) ? 1 : 0)) + (r & 1);
}
__device__ __forceinline__ constexpr bool hpartB(int t) { return t == 1 || t >= 5; }

template <int NV> __device__ __forceinline__ bool bad_vecs(const uint32_t (&v)[NV][4], uint32_t tag) {
    uint32_t bad = 0;
#pragma unroll
    for (int u = 0; u < NV; u += 2) {
        if (u + 1 < NV) {
            uint32_t x;
            asm("lop3.b32 %0, %1, %2, %3, 0x7e;" : "=r"(x) : "r"(v[u][0]), "r"(v[u + 1][0]), "r"(tag));
            if (u == 0) bad = x; else asm("or.b32 %0, %0, %1;" : "+r"(bad) : "r"(x));
        } else {
            asm("lop3.b32 %0, %1, %2, %0, 0xbe;" : "+r"(bad) : "r"(v[u][0]), "r"(tag));
        }
    }
    return __any_sync(0xffffffffu, bad & 1);
}

struct Ctx {
    uint32_t sb, sb16;
    uint32_t rel_addr;
    char* mb;
    int r, warp, layer;
    int budget;
    uint32_t eall;
    __device__ __forceinline__ uint32_t lane16() const { return launder((uint32_t)(size_t)mb) & 511; }
    __device__ __forceinline__ int lane() const { return lane16() >> 4; }
    __device__ __forceinline__ uint32_t park() const { return sb + OFF_PARK + warp * 2560 + lane16(); }
    __device__ __forceinline__ const char* box(int src) const { return mb + launder(src - r) * RBOX; }
};
__device__ __forceinline__ void sched_fence(Ctx& c) {
    asm volatile("{.reg .pred p; setp.eq.s32 p, %0, 0x400000%=;\nFENCE_%=: @p nanosleep.u32 1; @p bra.uni FENCE_%=;}" :: "r"(c.eall) : "memory");
}
__device__ __forceinline__ void wait_full(Ctx& c, int k) { mbar_wait(c.sb + BAR_FULL + (k % NSLOT) * 8, (k / NSLOT) & 1, c.budget); }
__device__ __forceinline__ void release(const Ctx& c, int k) {
    if (c.rel_addr != 0 && (k < NITEMS_L - NSLOT || c.layer == 0)) mbar_arrive_cluster(c.rel_addr + (k % NSLOT) * 8);
}
template <int K> __device__ __forceinline__ void order_wait(Ctx& c) {
    if (((ORDER >> K) & 1) && c.warp >= 4) mbar_wait(c.sb + BAR_ORD + K * 8, c.layer, c.budget);
}
template <int K> __device__ __forceinline__ void order_post(const Ctx& c) {
    if (((ORDER >> K) & 1) && c.warp == 0 && c.rel_addr != 0) mbar_arrive(c.sb + BAR_ORD + K * 8);
}
template <int NV> __device__ __forceinline__ void ld_vecs(uint32_t (&v)[NV][4], const char* p, int v0) {
#pragma unroll
    for (int u = 0; u < NV; u++) ldv(v[u], p + voff(v0 + u));
}
template <int NV> __device__ __forceinline__ void publish(const Ctx& c, uint32_t (&v)[NV][4], int v0, uint32_t tag) {
#pragma unroll
    for (int u = 0; u < NV; u++) {
        v[u][0] = launder(tagged(v[u][0], tag));
        stv(c.mb + voff(v0 + u), v[u][0], v[u][1], v[u][2], v[u][3]);
    }
}
template <int NV, class F> __device__ __forceinline__ void check_vecs(Ctx& c, uint32_t (&v)[NV][4], uint32_t tag, F reload) {
    while (bad_vecs(v, tag) && --c.budget >= 0) reload();
}

__device__ __forceinline__ void probe(Ctx& c, int src, int vec) {
    const char* pp = c.mb + ((src - c.r) * RBOX - (int)c.lane16() + voff(vec) + 496);
    uint32_t v;
    do {
        asm volatile("ld.relaxed.gpu.global.u32 %0, [%1];" : "=r"(v) : "l"(pp) : "memory");
    } while (__any_sync(0xffffffffu, !(v & 1u)) && --c.budget >= 0);
}

__device__ __forceinline__ void park_x(const Ctx& c, const uint32_t (&v)[5][4]) {
    const uint32_t a = c.park();
#pragma unroll
    for (int u = 0; u < 5; u++) stsm4(a + u * 512, v[u][0], v[u][1], v[u][2], v[u][3]);
}
__device__ __forceinline__ void unpark_x(const Ctx& c, uint32_t (&v)[5][4]) {
    const uint32_t a = c.park();
#pragma unroll
    for (int u = 0; u < 5; u++) ldsm4(v[u], a + u * 512);
}
__device__ __forceinline__ void unstage(Ctx& c, uint32_t (&v)[5][4], int odd, int which) {
    const int lane = c.lane();
    const uint32_t a = c.sb + STAGE_OFF + which * 20480 + (c.warp * 16 + (lane & 15)) * 160 + (lane >> 4) * 16;
    mbar_wait(c.sb + BAR_X + which * 8, 0, c.budget);
#pragma unroll
    for (int u = 0; u < 5; u++) ldsm4(v[u], u < 4 ? a + odd * 32 + u * 32 : a + 128 - odd * 128);
}
__device__ __forceinline__ void pack_x(uint32_t (&X)[5][4], const float (&v)[40]) {
#pragma unroll
    for (int u = 0; u < 5; u++)
#pragma unroll
        for (int i = 0; i < 4; i++) X[u][i] = pack2(v[8 * u + 2 * i], v[8 * u + 2 * i + 1]);
}
__device__ __forceinline__ void unpack_x(float (&v)[40], const uint32_t (&X)[5][4]) {
#pragma unroll
    for (int u = 0; u < 5; u++)
#pragma unroll
        for (int i = 0; i < 4; i++) { v[8 * u + 2 * i] = bf_lo(X[u][i]); v[8 * u + 2 * i + 1] = bf_hi(X[u][i]); }
}
__device__ __forceinline__ void store_out(const Ctx& c, const uint32_t (&X)[5][4], const CUtensorMap* tm, int blk) {
    const int lane = c.lane(), odd = c.r & 1;
    const uint32_t tile = c.sb + OFF_PARK + c.warp * 2560;
    const uint32_t a = tile + (lane & 15) * 160 + (lane >> 4) * 16;
#pragma unroll
    for (int u = 0; u < 5; u++) stsm4(u < 4 ? a + odd * 32 + u * 32 : a + 128 - odd * 128, X[u][0], X[u][1], X[u][2], X[u][3]);
    asm volatile("fence.proxy.async.shared::cta;" ::: "memory");
    __syncwarp();
    if (elect_one()) {
        asm volatile("cp.async.bulk.tensor.2d.global.shared::cta.bulk_group [%0, {%2, %3}], [%1];"
                     :: "l"(tm), "r"(tile), "r"(640 * (c.warp >> 2) + 80 * c.r), "r"(64 * blk + 16 * (c.warp & 3)) : "memory");
        asm volatile("cp.async.bulk.commit_group;" ::: "memory");
        asm volatile("cp.async.bulk.wait_group 0;" ::: "memory");
    }
    __syncwarp();
}

template <int NB, int V0, uint32_t TAG> struct Gather {
    uint32_t buf[NB][5][4];
    __device__ __forceinline__ uint32_t (&at(int t))[5][4] { return buf[(t - 1) % NB]; }
    __device__ __forceinline__ void fetch(Ctx& c, int t) { ld_vecs(at(t), c.box(slice_at(t, c.r)), V0); }
    __device__ __forceinline__ void check(Ctx& c, int t) { check_vecs(c, at(t), TAG, [&]() { fetch(c, t); }); }
};

struct GQKV {
    float m[96], r[24];
    template <bool INIT> __device__ __forceinline__ void step(const uint32_t (&a)[5][4], uint32_t sb16, int off, int odd) {
#pragma unroll
        for (int u = 0; u < 5; u++) {
            const uint64_t dm = mkdesc(sb16 + kstep(odd, u) * 128, off, 10240, 1024, 1), dr = mkdesc(sb16 + kstep(odd, u) * 32, off + 30720, 2560, 256, 3);
            if (INIT && u == 0) { wgmma_n192_init(m, a[u], dm); wgmma_n48_init(r, a[u], dr); }
            else { wgmma_n192_acc(m, a[u], dm); wgmma_n48_acc(r, a[u], dr); }
        }
    }
};
struct GW1 {
    float m[112];
    template <bool INIT> __device__ __forceinline__ void step(const uint32_t (&a)[5][4], uint32_t sb16, int off, int odd) {
#pragma unroll
        for (int u = 0; u < 5; u++) {
            const uint64_t d = mkdesc(sb16 + kstep(odd, u) * 64, off, 5120, 512, 2);
            if (INIT && u == 0) wgmma_n224_init(m, a[u], d); else wgmma_n224_acc(m, a[u], d);
        }
    }
};

template <int K0, int LAST, uint32_t TAG, class G, class A, class Hook>
__device__ __forceinline__ void ln_head(G& g, A& a, Ctx& c, const uint32_t (&own)[5][4], const float (&xv)[40],
                                        float& rsA, float& rsB, uint32_t (&ax)[4], Hook hook, int tl0) {
    sched_fence(c);
    wg_fence();
    g.template step<true>(own, c.sb16, slot_off(K0), c.r & 1);
    wg_commit();
    if (tl0) TL(tl0 + 1);
    sched_fence(c);
    float s[4] = {0.f, 0.f, 0.f, 0.f};
#pragma unroll
    for (int j = 0; j < 10; j++) {
        s[0] += xv[4 * j] + xv[4 * j + 1];
        s[1] = fmaf(xv[4 * j], xv[4 * j], fmaf(xv[4 * j + 1], xv[4 * j + 1], s[1]));
        s[2] += xv[4 * j + 2] + xv[4 * j + 3];
        s[3] = fmaf(xv[4 * j + 2], xv[4 * j + 2], fmaf(xv[4 * j + 3], xv[4 * j + 3], s[3]));
    }
    reg_fence(s);
    wait_full(c, K0 + 1);
    hook(-1);
    a.check(c, 1);
    a.fetch(c, 2);
    uint32_t sv[2][4];
    auto sfetch = [&]() {
        const int lane = c.lane();
        const char* p = c.mb + (((lane & 3) - c.r) * RBOX + (lane >> 2) * 16 - lane * 16);
        ldv(sv[0], p + voff(V_ST)); ldv(sv[1], p + voff(V_ST) + 4 * RBOX);
    };
#pragma unroll
    for (int t = 1; t <= LAST; t++) {
        sched_fence(c);
        if (tl0) TL(tl0 + 2 + t);
        wg_fence();
        g.template step<false>(a.at(t), c.sb16, slot_off(K0 + t), t == 1 ? (c.r & 1) ^ 1 : t & 1);
        wg_commit();
        wg_wait<1>();
        release(c, K0 + t - 1);
        wait_full(c, K0 + t + 1);
        if (t == 1) {
#pragma unroll
            for (int i = 0; i < 4; i++) {
                s[i] += __shfl_xor_sync(0xffffffffu, s[i], 1);
                s[i] += __shfl_xor_sync(0xffffffffu, s[i], 2);
            }
            const int lane = c.lane();
            if ((lane & 3) == 0)
                stv(c.mb + voff(V_ST) - lane * 12, tagged(__float_as_uint(s[0]), TAG), __float_as_uint(s[1]), __float_as_uint(s[2]), __float_as_uint(s[3]));
            sched_fence(c);
        }
        a.check(c, t + 1);
        if (t == LAST) check_vecs(c, sv, TAG, sfetch);
        a.fetch(c, t + 2);
        if (t == LAST - 1) sfetch();
        hook(t);
    }
#pragma unroll
    for (int i = 0; i < 4; i++) {
        s[i] = __uint_as_float(sv[0][i]) + __uint_as_float(sv[1][i]);
        s[i] += __shfl_xor_sync(0xffffffffu, s[i], 1);
        s[i] += __shfl_xor_sync(0xffffffffu, s[i], 2);
    }
    const float mA = s[0] * (1.f / DM), mB = s[2] * (1.f / DM);
    rsA = rsq(fmaxf(fmaf(-mA, mA, s[1] * (1.f / DM)), 0.f) + LN_EPS);
    rsB = rsq(fmaxf(fmaf(-mB, mB, s[3] * (1.f / DM)), 0.f) + LN_EPS);
    const uint32_t h = pack2(mA, mB);
    const uint32_t l = pack2(mA - bf_lo(h), mB - bf_hi(h));
    const bool on = (c.lane16() & 32) == 0;
    ax[0] = on ? __byte_perm(h, l, 0x5410) : 0u;
    ax[1] = on ? __byte_perm(h, l, 0x7632) : 0u;
    ax[2] = 0u; ax[3] = 0u;
    asm volatile("" : "+r"(ax[0]), "+r"(ax[1]), "+r"(ax[2]), "+r"(ax[3]), "+f"(rsA), "+f"(rsB));
    sched_fence(c);
}

__global__ void __cluster_dims__(2, 1, 1) __launch_bounds__(384, 1)
fused_layers_kernel(const __grid_constant__ Params prm, const __grid_constant__ CUtensorMap tmQM, const __grid_constant__ CUtensorMap tmQR,
                    const __grid_constant__ CUtensorMap tmWO, const __grid_constant__ CUtensorMap tmW1a, const __grid_constant__ CUtensorMap tmW1b,
                    const __grid_constant__ CUtensorMap tmW2, const __grid_constant__ CUtensorMap tmW2a, const __grid_constant__ CUtensorMap tmOut, const __grid_constant__ CUtensorMap tmX) {
    extern __shared__ __align__(1024) uint8_t smem_raw[];
    const uint32_t sb = smem_u32(smem_raw);
    const int warp = __shfl_sync(0xffffffffu, threadIdx.x >> 5, 0);
    const int lane = threadIdx.x & 31;
    const int cl = prm.role[blockIdx.x >> 1], p = blockIdx.x & 1;
    const int r = cl & 7, blk = (cl >> 3) * 2 + p;
    const int role = blk * 8 + r;
    TL(0); TLINIT

    if (warp >= 8 && elect_one()) {
        if (warp == 8) { prefetch_map(&tmQM); prefetch_map(&tmQR); prefetch_map(&tmX); }
        if (warp == 9) {
#pragma unroll
            for (int i = 0; i < NSLOT; i++) { mbar_init(sb + BAR_FULL + i * 8, 1); mbar_init(sb + BAR_EMPTY + i * 8, 16); }
            mbar_init(sb + BAR_STAGE, 16);
            mbar_init(sb + BAR_X, 1); mbar_init(sb + BAR_X + 8, 1);
            mbar_init(sb + BAR_CS, 3); mbar_init(sb + BAR_CS + 8, 3);
#pragma unroll
            for (int i = 0; i < NORD; i++) mbar_init(sb + BAR_ORD + i * 8, 2);
            asm volatile("fence.mbarrier_init.release.cluster;" ::: "memory");
        }
    }
    __syncwarp();
    asm volatile("barrier.cluster.arrive.relaxed.aligned;" ::: "memory");
    uint32_t etag0;
    asm volatile("{.reg .pred p; setp.ne.s32 p, %2, 8; mov.b32 %0, 0; @p ld.relaxed.gpu.global.u32 %0, [%1];}"
                 : "=r"(etag0) : "l"(prm.scr + (uint32_t)(G_EPOCH + role * 128 + lane * 4)), "r"(warp) : "memory");
    auto load_x = [&](int i) {
        mbar_expect(sb + BAR_X + i * 8, 20480);
        tma2d(sb + STAGE_OFF + i * 20480, &tmX, 80 * (r ^ i), 64 * blk, sb + BAR_X + i * 8);
        tma2d(sb + STAGE_OFF + i * 20480 + 10240, &tmX, 640 + 80 * (r ^ i), 64 * blk, sb + BAR_X + i * 8);
    };
    TL(10);
    asm volatile("barrier.cluster.wait.aligned;" ::: "memory");
    if (warp == 8) {
        TL(1);
        if (elect_one()) {
#pragma unroll 1
            for (int i = 0; i < 2; i++) {
                const uint32_t base = sb + i * slot_off(1), bar = sb + BAR_FULL + i * 8;
                const int row = 80 * (r ^ i);
                mbar_expect(bar, 38400);
                tma2d_mc(base + p * 10240, &tmQM, main_col(r) + 640 * p, row, bar);
                if (p) tma2d_mc(base + 20480, &tmQM, main_col(r) + 1280, row, bar);
                else tma3d_mc(base + 30720, &tmQR, rem_col(r), row, 0, bar);
                if (i == 0) { load_x(0); load_x(1); }
            }
        }
        __syncwarp();
        TL(2);
    }

    if (warp >= 8) {
        int budget = SPIN_BUDGET;
        asm volatile("setmaxnreg.dec.sync.aligned.u32 %0;" :: "n"(REG_HELP));
        if (warp == 8) {
            TL(5);
            if (elect_one()) {
                int slot = 2, use = 0;
#pragma unroll 1
                for (int i = 2; i < NITEMS; i++) {
                    const int k = i >= NITEMS_L ? i - NITEMS_L : i;
                    const uint32_t base = sb + slot_off(slot), bar = sb + BAR_FULL + slot * 8;
                    if (use > 0) mbar_wait(sb + BAR_EMPTY + slot * 8, (use - 1) & 1, budget);
                    if (i == 3) mbar_wait(sb + BAR_STAGE, 0, budget);
                    if (i < NSLOT) mbar_wait(sb + BAR_FULL + (i - 2) * 8, 0, budget);
                    const int q = (k + p) & 1;
                    if (k < 8) {
                        const int np = k < 5 ? 3 : 2, row = 80 * slice_at(k, r), col = main_col(r) + 640 * (3 - np);
                        mbar_expect(bar, np * 10240 + 7680);
                        if (q) {
                            tma2d_mc(base, &tmQM, col, row, bar);
                            tma2d_mc(base + 10240, &tmQM, col + 640, row, bar);
                        } else {
                            if (np == 3) tma2d_mc(base + 20480, &tmQM, col + 1280, row, bar);
                            tma3d_mc(base + np * 10240, &tmQR, rem_col(r), row, 0, bar);
                        }
                    } else if (k == 8) {
                        mbar_expect(bar, 30720);
                        tma2d_mc(base + q * 10240, &tmQM, main_col(r), 80 * slice_at(5 + q, r), bar);
                        if (!q) tma2d_mc(base + 20480, &tmQM, main_col(r), 80 * slice_at(7, r), bar);
                    } else if (k < IT_W1) {
                        mbar_expect(bar, 30720);
                        const int row = 80 * slice_at(2 * (k - IT_WO) + p, r);
#pragma unroll
                        for (int a = 0; a < 3; a++) tma2d_mc(base + p * 15360 + a * 5120, &tmWO, a < 2 ? main_col(r) + 32 * a : rem_col(r), row, bar);
                    } else if (k < IT_W2) {
                        const bool full = k < IT_W1 + 6, pb = full ? q : k == IT_W1 + 7;
                        mbar_expect(bar, full ? 35840 : pb ? 40960 : 30720);
                        const int row = 80 * slice_at(full ? k - IT_W1 : 6 + p, r);
                        if (pb) tma3d_mc(base + (full ? 0 : p * 20480), &tmW1b, 0, row, 7 * r, bar);
                        else tma3d_mc(base + (full ? 20480 : p * 15360), &tmW1a, 0, row, 7 * r + 4, bar);
                    } else if (k < IT_W2 + 8) {
                        const int st = k - IT_W2, a0 = st < 6 ? 0 : 2;
                        const bool pb = hpartB(st);
                        const int atom = pb ? 8192 : 6144;
                        mbar_expect(bar, (5 - a0) * atom);
                        const int row = 224 * hsrc_at(st, r) + (pb ? 0 : 128);
#pragma unroll 1
                        for (int a = a0 + q; a < 5; a += 2)
                            tma2d_mc(base + (a - a0) * atom, pb ? &tmW2 : &tmW2a, a < 4 ? main_col(r ^ (a >> 1)) + 32 * (a & 1) : 160 * (r >> 1) + 64, row, bar);
                    } else {
                        mbar_expect(bar, 32768);
                        const int row = 224 * hsrc_at(6 + p, r);
                        tma2d_mc(base + p * 16384, &tmW2, main_col(r), row, bar);
                        tma2d_mc(base + p * 16384 + 8192, &tmW2, main_col(r) + 32, row, bar);
                    }
                    if (i == 2) TL(3);
                    if (i == 3) { prefetch_map(&tmWO); prefetch_map(&tmW1a); prefetch_map(&tmW1b); prefetch_map(&tmW2); prefetch_map(&tmW2a); }
                    if (i == NITEMS - 1) prefetch_map(&tmOut);
                    if (++slot == NSLOT) { slot = 0; use++; }
                }
            }
            __syncwarp();
            TLDUMP(16);
        } else {
#pragma unroll 1
            for (int i = threadIdx.x - 288; i < XTRA_BYTES / 16; i += 96)
                asm volatile("st.shared.v4.u32 [%0], {%1,%1,%1,%1};" :: "r"(sb + OFF_XQM + i * 16), "r"(0) : "memory");
            asm volatile("bar.sync 5, 96;" ::: "memory");
            const uint32_t etag = (launder(etag0) & 1u) ^ 1u;
            if (lane < 10) {
                char* cs = prm.scr + (uint32_t)(G_CS + (r * 6 + warp - 9) * 5120 + blk * 320 + lane * 32);
#pragma unroll
                for (int i = 0; i < 4; i++) stv(cs + (i >> 1) * 3 * 5120 + (i & 1) * 16, etag ^ 1u, 0u, 0u, 0u);
            }
            mbar_wait(sb + BAR_X, 0, budget);
            TLH(11);
#pragma unroll 1
            for (int mat = 0; mat < 2; mat++) {
                const int lane = launder(threadIdx.x & 31), j = launder(warp) - 9;
                const int rp = lane < 30 ? (lane * 13) >> 7 : 2, ch = lane < 30 ? lane - 10 * rp : 0;
                const int col = mat ? 224 * r + 80 * j + 8 * ch : 640 * j + 80 * r + 8 * ch;
                const bool valid = !mat || (10 * j + ch < 28 && col < DFF);
                float a[8] = {0.f, 0.f, 0.f, 0.f, 0.f, 0.f, 0.f, 0.f};
                auto sum_rows = [&](const __nv_bfloat16* w0, auto pitch_c) {
                    constexpr int PITCH = decltype(pitch_c)::value;
                    const char* src = reinterpret_cast<const char*>(w0 + (40 * blk + rp) * PITCH + (valid ? col : 0));
#pragma unroll 1
                    for (int h = 0; h < 2; h++) {
                        uint32_t w[7][4];
                        const bool last = h == 0 || rp == 0;
#pragma unroll
                        for (int i = 0; i < 6; i++) ldv(w[i], src + i * 6 * PITCH);
                        ldv(w[6], src + (last ? 36 * PITCH : 0));
#pragma unroll
                        for (int i = 0; i < 7; i++)
#pragma unroll
                            for (int e = 0; e < 4; e++) {
                                const uint32_t v = (i < 6 || last) ? w[i][e] : 0u;
                                a[2 * e] += bf_lo(v); a[2 * e + 1] += bf_hi(v);
                            }
                        src += 42 * PITCH;
                    }
                };
                auto prefetch_w1 = [&]() {
                    const int c1 = 224 * r + 80 * j + 8 * ch;
                    if (10 * j + ch < 28 && c1 < DFF && !(ch & 1)) {
                        const __nv_bfloat16* pf = prm.w1 + (40 * blk + rp) * DFF + c1;
#pragma unroll
                        for (int i = 0; i < 13; i++) asm volatile("prefetch.global.L2 [%0];" :: "l"(pf + 3 * i * DFF));
                        if (rp == 0) asm volatile("prefetch.global.L2 [%0];" :: "l"(pf + 39 * DFF));
                    }
                    __syncwarp();
                };
                if (mat == 0) {
                    sum_rows(prm.wqkv, IntC<DQKV>());
                } else {
                    sum_rows(prm.w1, IntC<DFF>());
                }
                char* cs = prm.scr + (uint32_t)(G_CS + ((r * 2 + mat) * 3 + j) * 5120);
#pragma unroll
                for (int i = 0; i < 8; i++) {
                    a[i] += __shfl_down_sync(0xffffffffu, a[i], 10) + __shfl_down_sync(0xffffffffu, a[i], 20);
                    a[i] = valid ? a[i] : 0.f;
                }
                if (lane < 10) {
                    char* dst = cs + blk * 320 + lane * 32;
                    stv(dst, tagged(__float_as_uint(a[0]), etag), __float_as_uint(a[1]), __float_as_uint(a[2]), __float_as_uint(a[3]));
                    stv(dst + 16, tagged(__float_as_uint(a[4]), etag), __float_as_uint(a[5]), __float_as_uint(a[6]), __float_as_uint(a[7]));
                }
                if (mat == 0) {
                    TLH(12);
                    prefetch_w1();
                }
                cs += (lane < 20 ? lane : 0) * 16;
                a[0] = 0.f; a[1] = 0.f; a[2] = 0.f; a[3] = 0.f;
#pragma unroll 1
                for (int b0 = 0; b0 < 2;) {
                    uint32_t v[8][4];
#pragma unroll
                    for (int i = 0; i < 8; i++) ldv(v[i], cs + i * 320);
                    if (bad_vecs(v, etag) && --budget >= 0) continue;
#pragma unroll
                    for (int i = 0; i < 8; i++)
#pragma unroll
                        for (int e = 0; e < 4; e++) a[e] -= __uint_as_float(v[i][e]);
                    b0++;
                    cs += 8 * 320;
                }
                if (mat == 0) TLH(14);
                const uint32_t h0 = pack2(a[0], a[1]), h1 = pack2(a[2], a[3]);
                const uint32_t l0 = pack2(a[0] - bf_lo(h0), a[1] - bf_hi(h0)), l1 = pack2(a[2] - bf_lo(h1), a[3] - bf_hi(h1));
                const int cc = 4 * launder(lane), cm = cc - 16 * (r & 1), cw = 80 * j + cc;
                const bool mainp = cm >= 0 && cm < 64;
                const uint32_t sh = mat ? 6 : mainp ? 7 : 5;
                const uint32_t ad = sb + (mat ? OFF_XW1 + (cw >> 5) * 512 + (cw & 31) * 2 : mainp ? OFF_XQM + j * 1024 + cm * 2 : OFF_XQR + j * 256 + (cc & 15) * 2);
                if (cc < 80 && (!mat || cw < 224)) {
#pragma unroll
                    for (int row = 0; row < 4; row++) {
                        const uint32_t o = row << sh;
                        asm volatile("st.shared.v2.u32 [%0], {%1,%2};" :: "r"((ad + o) ^ ((o >> 7) << 4)), "r"(row < 2 ? h0 : l0), "r"(row < 2 ? h1 : l1) : "memory");
                    }
                }
                asm volatile("fence.proxy.async.shared::cta;" ::: "memory");
                __syncwarp();
                if (lane == 0) mbar_arrive(sb + BAR_CS + mat * 8);
                TLH(6 + mat);
            }
        }
    } else {
        TL(11);
        TL(12);
        __syncwarp();
        asm volatile("setmaxnreg.inc.sync.aligned.u32 %0;" :: "n"(REG_CONS));
        TL(14);
        Ctx c;
        c.sb = sb; c.sb16 = (sb & 0x3FFFF) >> 4; c.r = r; c.warp = warp; c.layer = 0; c.budget = SPIN_BUDGET; c.eall = __ballot_sync(0xffffffffu, !(launder(etag0) & 1u));
        c.mb = reinterpret_cast<char*>(__shfl_sync(0xffffffffu, reinterpret_cast<size_t>(prm.scr + (uint32_t)(blk * BBOX + r * RBOX + warp * WBOX + lane * 16)), lane));
        asm volatile("mapa.shared::cluster.u32 %0, %1, %2;" : "=r"(c.rel_addr) : "r"(sb + BAR_EMPTY), "r"(lane & 1));
        c.rel_addr = __shfl_sync(0xffffffffu, lane < 2 ? c.rel_addr : 0, lane);
        uint32_t X[5][4];
        float xv[40];
        unstage(c, X, r & 1, 0);
        TL(15);
        wait_full(c, 0);
        TL(13);
        unpack_x(xv, X);
        park_x(c, X);
        TL(1);

        const int r_ = r, blk_ = blk, warp_ = warp;
#define PHASE_IDS const int r = launder(r_), blk = launder(blk_), warp = launder(warp_), wg = warp >> 2, w = warp & 3; \
                  c.r = r; c.warp = warp; c.sb = launder(sb); c.sb16 = (c.sb & 0x3FFFF) >> 4; const uint32_t etag = launder(c.eall) & 1u; (void)etag; (void)blk; (void)wg; (void)w;
#pragma unroll 1
        for (int layer = 0;; layer++) {
            c.layer = layer;
            float rsA, rsB;
            uint32_t O[5][4];
            {
                PHASE_IDS
                GQKV q;
                Gather<3, V_X, 1u> ga;
                uint32_t ax[4];
                auto hook = [&](int st) {
                    if (st == -1) {
                        if (layer == 0) {
                            unstage(c, ga.buf[0], (r & 1) ^ 1, 1);
#pragma unroll
                            for (int u = 0; u < 5; u++) ga.buf[0][u][0] |= 1u;
                            if (c.rel_addr != 0) mbar_arrive_cluster(c.rel_addr + (BAR_STAGE - BAR_EMPTY));
                        } else {
                            ga.fetch(c, 1);
                        }
                    }
                    if (st >= 1 && layer == 0) {
                        if (st == CLR_HALO && w == 3) {
#pragma unroll
                            for (int u = 0; u < 6; u++) stv(c.mb + voff(V_HALO + u), etag ^ 1u, 0u, 0u, 0u);
                        }
#pragma unroll
                        for (int u = 0; u < 5; u++)
                            if (st == ((CLR_O >> (4 * u)) & 15)) stv(c.mb + voff(V_O + u), 0u, 0u, 0u, 0u);
                    }
                };
                publish(c, X, V_X, 1u);
                ln_head<0, 4, 1u>(q, ga, c, X, xv, rsA, rsB, ax, hook, (TLSEL == 1 + layer * 4) ? 50 : 0);
                float qm[32], kv[64];
                wg_wait<0>();
                reg_fence(q.m);
                rename<32, 0>(qm, q.m);
                rename<64, 32>(kv, q.m);
#pragma unroll
                for (int st = 5; st < 8; st++) {
                    if (st == 7) order_wait<0>(c);
                    wg_fence();
#pragma unroll
                    for (int u = 0; u < 5; u++) {
                        wgmma_n128_acc(kv, ga.at(st)[u], mkdesc(c.sb16, slot_off(st) + kstep(st & 1, u) * 2048, 10240, 1024, 1));
                        wgmma_n48_acc(q.r, ga.at(st)[u], mkdesc(c.sb16, slot_off(st) + 20480 + kstep(st & 1, u) * 512, 2560, 256, 3));
                    }
                    if (st == 7) {
                        wgmma_n128_acc(kv, ax, mkdesc(c.sb16, OFF_XQM + 1024, 1024, 0, 1));
                        wgmma_n48_acc(q.r, ax, mkdesc(c.sb16, OFF_XQR, 256, 0, 3));
                    }
                    wg_commit();
                    if (st == 7) order_post<0>(c);
                    if (st > 5) wg_wait<1>();
                    release(c, st - 1);
                    wait_full(c, st + 1);
                    if (st == 5) {
                        ga.check(c, 6);
                        ga.fetch(c, 7);
                        sched_fence(c);
                    }
                    if (st == 6) {
                        if (layer == 0) mbar_wait(c.sb + BAR_CS, 0, c.budget);
                        ga.check(c, 7);
                    }
                }
                float rk1[2], rk2[2];
                {
                    const int t8 = (c.lane16() >> 1) & 24;
#pragma unroll
                    for (int e = 0; e < 2; e++) {
                        rk2[e] = __shfl_sync(0xffffffffu, rsB, t8 + 4 * e);
                        rk1[e] = __shfl_sync(0xffffffffu, rsA, t8 + 4 * e);
                    }
                }
                auto q_steps = [&](int n0, int n1) {
                    wg_fence();
#pragma unroll
                    for (int n = n0; n < n1; n++) {
                        if (n < 15) wgmma_n64_acc(qm, ga.at(5 + n / 5)[n % 5], mkdesc(c.sb16, slot_off(8) + (n / 5 * 5 + kstep((5 + n / 5) & 1, n % 5)) * 2048, 1024, 1024, 1));
                        else wgmma_n64_acc(qm, ax, mkdesc(c.sb16, OFF_XQM, 1024, 0, 1));
                    }
                    wg_commit();
                };
                q_steps(0, 7);
                wg_wait<1>();
                reg_fence(kv);
                reg_fence(q.r);
                release(c, 7);
                TL(2 + layer * 16);
                uint32_t T[3][10][2];
                auto pack_tiles = [&](int pc, int h, bool odd) {
#pragma unroll
                    for (int j = 0; j < 10; j++) {
                        const bool isrem = odd ? j < 2 : j >= 8;
                        const int e = isrem ? pc * 8 + 4 * (j & 1) + 2 * h : 4 * ((odd ? j + 6 : j) & 7) + 2 * h;
                        if (isrem) T[pc][j][h] = pack2(q.r[e], q.r[e + 1]);
                        else T[pc][j][h] = pc == 0 ? pack2(qm[e], qm[e + 1]) : pack2(kv[(pc - 1) * 32 + e], kv[(pc - 1) * 32 + e + 1]);
                    }
                };
                if (r & 1) { pack_tiles(1, 1, true); pack_tiles(2, 1, true); }
                else { pack_tiles(1, 1, false); pack_tiles(2, 1, false); }
                auto hreg = [&](int n) -> uint32_t& { return n < 8 ? T[1][n + (n + 2) / 4][1] : n < 10 ? T[1][5 * n - 38][1] : T[2][n - 10][1]; };
                if (w == 3) {
                    char* hg = c.mb + layer * (2 * PLANE);
#pragma unroll
                    for (int u = 0; u < 5; u++) {
                        hreg(4 * u) = tagged(hreg(4 * u), etag);
                        stv(hg + voff(V_HALO + u), hreg(4 * u), hreg(4 * u + 1), hreg(4 * u + 2), hreg(4 * u + 3));
                    }
                    stv(hg + voff(V_HALO + 5), tagged(__float_as_uint(rk2[0]), etag), __float_as_uint(rk2[1]), 0u, 0u);
                }
                if (r & 1) { pack_tiles(1, 0, true); pack_tiles(2, 0, true); }
                else { pack_tiles(1, 0, false); pack_tiles(2, 0, false); }
                unpark_x(c, X);
                q_steps(7, 16);
                if (w < 3) {
                    const uint32_t hs = c.park();
#pragma unroll
                    for (int u = 0; u < 5; u++) stsm4(hs + u * 512, hreg(4 * u), hreg(4 * u + 1), hreg(4 * u + 2), hreg(4 * u + 3));
                    if (c.lane16() < 64) asm volatile("st.shared.v2.f32 [%0], {%1,%2};" :: "r"(c.sb + OFF_RK + warp * 32 + (c.lane16() >> 1)), "f"(rk2[0]), "f"(rk2[1]) : "memory");
                }
                asm volatile("bar.sync %0, 128;" :: "r"(1 + wg) : "memory");
                uint32_t H[6][4];
                auto hfetch = [&]() { ld_vecs(H, c.mb + (3 * WBOX - BBOX) + layer * (2 * PLANE), V_HALO); };
                if (w > 0) {
                    const uint32_t hs = c.park() - 2560;
                    ldsm4(H[0], hs); ldsm4(H[1], hs + 512);
                    asm volatile("ldmatrix.sync.aligned.m8n8.x2.shared.b16 {%0,%1}, [%2];" : "=r"(H[2][0]), "=r"(H[2][1]) : "r"(hs + 1024) : "memory");
                    asm volatile("ldmatrix.sync.aligned.m8n8.x2.trans.shared.b16 {%0,%1}, [%2];" : "=r"(H[2][2]), "=r"(H[2][3]) : "r"(hs + 1280) : "memory");
                    ldsm4t(H[3], hs + 1536); ldsm4t(H[4], hs + 2048);
                    asm volatile("ld.shared.v2.u32 {%0,%1}, [%2];" : "=r"(H[5][0]), "=r"(H[5][1]) : "r"(c.sb + OFF_RK + warp * 32 - 32 + ((c.lane16() >> 1) & 24)) : "memory");
                    H[5][2] = 0u; H[5][3] = 0u;
                } else if (blk > 0) {
                    hfetch();
                } else {
#pragma unroll
                    for (int u = 0; u < 6; u++) { H[u][0] = 0u; H[u][1] = 0u; H[u][2] = 0u; H[u][3] = 0u; }
                }
                auto hK = [&](int j) { return j == 2 ? H[2][0] : j == 7 ? H[2][1] : H[(j - (j + 2) / 5) >> 2][(j - (j + 2) / 5) & 3]; };
                auto hV = [&](int j) { return H[(j + 10) >> 2][(j + 10) & 3]; };
                uint32_t Vt1[10], Vt2[10];
#pragma unroll
                for (int j = 0; j < 10; j++) { Vt1[j] = movm(T[2][j][0]); Vt2[j] = movm(T[2][j][1]); }
                wg_wait<0>();
                reg_fence(qm);
                release(c, 8);
                if (r & 1) { pack_tiles(0, 0, true); pack_tiles(0, 1, true); }
                else { pack_tiles(0, 0, false); pack_tiles(0, 1, false); }
                TL(3 + layer * 16);
                const int g = c.lane() >> 2, t = c.lane() & 3;
                const bool sel0 = 2 * t > g, sel1 = 2 * t + 1 > g;
                const float cs = 0.22360679774997896f * 1.4426950408889634f;
                const float kB0 = sel0 ? rk1[0] : rk2[0], kB1 = sel1 ? rk1[1] : rk2[1];
                const float fB0 = rsB * cs * kB0, fB1 = rsB * cs * kB1;
                float lA0[4], lA1[4], lB0[4], lB1[4];
                uint32_t qs[4][2];
#pragma unroll
                for (int h = 0; h < 4; h++) {
                    const int f0 = 5 * (h >> 1) + 3 * (h & 1), f1 = f0 + 1, s = 5 * (h >> 1) + 2;
                    const bool keep = (h & 1) ? (t >= 2) : (t < 2);
                    qs[h][0] = keep ? T[0][s][0] : 0u; qs[h][1] = keep ? T[0][s][1] : 0u;
                    float s1[4], s2[4];
                    mma_k8_init(s1, qs[h][0], qs[h][1], T[1][s][0]);
                    mma_k8_init(s2, qs[h][0], qs[h][1], T[1][s][1]);
                    mma_k16_acc(s1, T[0][f0][0], T[0][f0][1], T[0][f1][0], T[0][f1][1], T[1][f0][0], T[1][f1][0]);
                    mma_k16_acc(s2, T[0][f0][0], T[0][f0][1], T[0][f1][0], T[0][f1][1], T[1][f0][1], T[1][f1][1]);
                    lA0[h] = s1[0]; lA1[h] = s1[1];
                    lB0[h] = (sel0 ? s1[2] : s2[2]) * fB0;
                    lB1[h] = (sel1 ? s1[3] : s2[3]) * fB1;
                }
                wait_full(c, IT_WO);
                if (w == 0 && blk > 0) {
                    check_vecs(c, H, etag, hfetch);
#pragma unroll
                    for (int n = 10; n < 20; n++) H[n >> 2][n & 3] = movm(H[n >> 2][n & 3]);
                }
                const bool first = (blk == 0) && (w == 0);
                const float kA0 = sel0 ? __uint_as_float(H[5][0]) : rk1[0], kA1 = sel1 ? __uint_as_float(H[5][1]) : rk1[1];
                const float fA0 = rsA * cs * kA0, fA1 = rsA * cs * kA1;
                const float bA0 = (first && sel0) ? -INFINITY : 0.f, bA1 = (first && sel1) ? -INFINITY : 0.f;
                const uint32_t M = (sel0 ? 0x0000ffffu : 0u) | (sel1 ? 0xffff0000u : 0u);
#pragma unroll
                for (int h = 0; h < 4; h++) {
                    const int f0 = 5 * (h >> 1) + 3 * (h & 1), f1 = f0 + 1, s = 5 * (h >> 1) + 2;
                    float s0[4];
                    mma_k8_init(s0, qs[h][0], qs[h][1], hK(s));
                    mma_k16_acc(s0, T[0][f0][0], T[0][f0][1], T[0][f1][0], T[0][f1][1], hK(f0), hK(f1));
                    lA0[h] = fmaf(sel0 ? s0[0] : lA0[h], fA0, bA0);
                    lA1[h] = fmaf(sel1 ? s0[1] : lA1[h], fA1, bA1);
                }
                uint32_t pA[4], pB[4];
#pragma unroll
                for (int h = 0; h < 4; h++) {
                    float mA = fmaxf(lA0[h], lA1[h]), mB = fmaxf(lB0[h], lB1[h]);
                    mA = fmaxf(mA, __shfl_xor_sync(0xffffffffu, mA, 1));
                    mB = fmaxf(mB, __shfl_xor_sync(0xffffffffu, mB, 1));
                    mA = fmaxf(mA, __shfl_xor_sync(0xffffffffu, mA, 2));
                    mB = fmaxf(mB, __shfl_xor_sync(0xffffffffu, mB, 2));
                    const float eA0 = ex2(lA0[h] - mA), eA1 = ex2(lA1[h] - mA), eB0 = ex2(lB0[h] - mB), eB1 = ex2(lB1[h] - mB);
                    float sA = eA0 + eA1, sB = eB0 + eB1;
                    sA += __shfl_xor_sync(0xffffffffu, sA, 1);
                    sB += __shfl_xor_sync(0xffffffffu, sB, 1);
                    sA += __shfl_xor_sync(0xffffffffu, sA, 2);
                    sB += __shfl_xor_sync(0xffffffffu, sB, 2);
                    const float iA = rcp(sA), iB = rcp(sB);
                    pA[h] = pack2(eA0 * kA0 * iA, eA1 * kA1 * iA);
                    pB[h] = pack2(eB0 * kB0 * iB, eB1 * kB1 * iB);
                }
#pragma unroll
                for (int h = 0; h < 4; h++) {
                    const int f0 = 5 * (h >> 1) + 3 * (h & 1), s = 5 * (h >> 1) + 2;
                    const uint32_t ap = pA[h] & M, a0 = pA[h] & ~M, a1 = pB[h] & M, a3 = pB[h] & ~M;
#pragma unroll
                    for (int i = 0; i < 3; i++) {
                        const int j = i < 2 ? f0 + i : s;
                        float o[4];
                        mma_k8_init(o, ap, 0u, hV(j));
                        mma_k16_acc(o, a0, a1, 0u, a3, Vt1[j], Vt2[j]);
                        const uint32_t o0 = pack2(o[0], o[1]), o1 = pack2(o[2], o[3]);
                        uint32_t& d0 = O[j >> 1][2 * (j & 1)];
                        uint32_t& d1 = O[j >> 1][2 * (j & 1) + 1];
                        if (i < 2 || (h & 1) == 0) { d0 = o0; d1 = o1; }
                        else { d0 = t >= 2 ? o0 : d0; d1 = t >= 2 ? o1 : d1; }
                    }
                }
                publish(c, O, V_O, 1u);
            }
            TL(4 + layer * 16);
            {
                PHASE_IDS
                Gather<7, V_O, 1u> ga;
                sched_fence(c);
                unpack_x(xv, X);
#pragma unroll
                for (int st = 0; st < 8; st++) {
                    if (st == 6) order_wait<1>(c);
                    wg_fence();
#pragma unroll
                    for (int u = 0; u < 5; u++)
                        wgmma_n80_acc(xv, st == 0 ? O[u] : ga.at(st > 0 ? st : 1)[u], mkdesc(c.sb16, slot_off(IT_WO + st / 2) + (st & 1) * 15360 + u * 1024, 5120, 512, 2));
                    wg_commit();
                    if (st == 7) order_post<1>(c);
                    if (st > 0 && (st & 1) == 0) { wg_wait<1>(); release(c, IT_WO + st / 2 - 1); }
                    const bool batch = st == 0 || st == WO_B1 || st == WO_B2;
                    if (st & 1) wait_full(c, IT_WO + st / 2 + 1); else if (batch) sched_fence(c);
                    if (st == 0) {
#pragma unroll
                        for (int i = 1; i <= WO_B1; i++) ga.fetch(c, i);
                    }
                    if (batch) {
                        const int e0 = st == 0 ? WO_B1 : st == WO_B1 ? WO_B2 : 7, e1 = st == 0 ? WO_B2 : 7;
#pragma unroll
                        for (int i = st + 1; i <= e0; i++) ga.check(c, i);
#pragma unroll
                        for (int i = e0 + 1; i <= e1; i++) ga.fetch(c, i);
                        if (e1 > e0) sched_fence(c);
                    }
                    if (TLSEL == 2 + layer * 4) TL(50 + st);
                }
                wg_wait<0>();
                reg_fence(xv);
                release(c, IT_W1 - 1);
                TL(5 + layer * 16);
                pack_x(X, xv);
                if (DBG_STAGE == 1 + 2 * layer) store_out(c, X, &tmOut, blk);
                park_x(c, X);
                publish(c, X, V_X, 0u);
            }
            TL(6 + layer * 16);
            {
                PHASE_IDS
                const uint32_t ltag = layer ^ 1u;
                uint32_t Ha[6][4], Hb[8][4];
                {
                    GW1 f;
                    Gather<3, V_X, 0u> ga;
                    uint32_t ax[4];
                    ln_head<IT_W1, 5, 0u>(f, ga, c, X, xv, rsA, rsB, ax, [&](int st) {
                        if (st == -1) ga.fetch(c, 1);
                        if (st == 2 && layer == 0) {
                            stv(c.mb + voff(V_HB + 7), 0u, 0u, 0u, 0u);
                            stv(c.mb + voff(V_HA + 5), 0u, 0u, 0u, 0u);
                        }
                        if (st == 3 && layer == 0 && w == 3) {
#pragma unroll
                            for (int u = 0; u < 6; u++) stv(c.mb + voff(V_HALO + 10 + u), etag ^ 1u, 0u, 0u, 0u);
                        }
                    }, (TLSEL == 3 + layer * 4) ? 50 : 0);
                    float fa[48], fb[64];
                    if (layer == 0) mbar_wait(c.sb + BAR_CS + 8, 0, c.budget);
                    order_wait<2>(c);
                    wg_wait<0>();
                    reg_fence(f.m);
                    rename<64, 0>(fb, f.m);
                    rename<48, 64>(fa, f.m);
#pragma unroll
                    for (int st = 6; st < 8; st++) {
                        wg_fence();
#pragma unroll
                        for (int u = 0; u < 5; u++)
                            wgmma_n96_acc(fa, ga.at(st)[u], mkdesc(c.sb16, slot_off(IT_W1 + 6) + (st - 6) * 15360 + kstep(st & 1, u) * 1024, 5120, 512, 2));
                        if (st == 6) {
                            order_post<2>(c);
                            release(c, IT_W1 + 5);
                            wait_full(c, IT_W1 + 7);
                            ga.check(c, 7);
                        }
                    }
                    wgmma_n96_acc(fa, ax, mkdesc(c.sb16, OFF_XW1 + 2048, 512, 0, 2));
                    wg_commit();
                    auto b_steps = [&](int n0, int n1) {
                        wg_fence();
#pragma unroll
                        for (int n = n0; n < n1; n++) {
                            if (n < 10) wgmma_n128_acc(fb, ga.at(6 + n / 5)[n % 5], mkdesc(c.sb16, slot_off(IT_W1 + 7) + (n / 5) * 20480 + kstep(n / 5, n % 5) * 1024, 5120, 512, 2));
                            else wgmma_n128_acc(fb, ax, mkdesc(c.sb16, OFF_XW1, 512, 0, 2));
                        }
                        wg_commit();
                    };
                    b_steps(0, 7);
                    wait_full(c, IT_W2);
                    wg_wait<1>();
                    reg_fence(fa);
                    release(c, IT_W1 + 6);
                    TL(7 + layer * 16);
#pragma unroll
                    for (int k = 0; k < 6; k++)
#pragma unroll
                        for (int i = 0; i < 4; i++) Ha[k][i] = pack2_relu(fa[8 * k + 2 * i], fa[8 * k + 2 * i + 1]);
                    publish(c, Ha, V_HA, ltag);
                    sched_fence(c);
                    b_steps(7, 11);
                    wg_wait<0>();
                    reg_fence(fb);
#pragma unroll
                    for (int k = 0; k < 8; k++)
#pragma unroll
                        for (int i = 0; i < 4; i++) Hb[k][i] = pack2_relu(fb[8 * k + 2 * i], fb[8 * k + 2 * i + 1]);
                    sched_fence(c);
                }
                float acc[80];
                uint32_t bufa[3][6][4], bufb[3][8][4];
                auto step_a = [&](int st, const uint32_t (&a)[6][4]) {
                    wg_fence();
#pragma unroll
                    for (int k = 0; k < 6; k++) {
                        const uint64_t d = mkdesc(c.sb16, slot_off(IT_W2 + st) + k * 1024, 6144, 512, 2);
                        if (st == 0 && k == 0) wgmma_n160_init(acc, a[k], d); else wgmma_n160_acc(acc, a[k], d);
                    }
                    wg_commit();
                };
                auto step_b = [&](int st, const uint32_t (&a)[8][4]) {
                    wg_fence();
#pragma unroll
                    for (int k = 0; k < 8; k++) wgmma_n160_acc(acc, a[k], mkdesc(c.sb16, slot_off(IT_W2 + st) + k * 1024, 8192, 512, 2));
                    wg_commit();
                };
                auto hprobe = [&](int vec) { if (layer == 0) probe(c, ((c.lane16() >> 3) & 6) + (r & 1), vec); };
                auto hfetch = [&](int st) {
                    if (st < 5) ld_vecs(bufa[st < 5 ? st - 2 : 0], c.box(hsrc_at(st, r)), V_HA);
                    else ld_vecs(bufb[st < 5 ? 0 : st - 5], c.box(hsrc_at(st, r)), V_HB);
                };
                auto hcheck = [&](int st) {
                    if (st < 5) check_vecs(c, bufa[st < 5 ? st - 2 : 0], ltag, [&]() { hfetch(st); });
                    else check_vecs(c, bufb[st < 5 ? 0 : st - 5], ltag, [&]() { hfetch(st); });
                };
                step_a(0, Ha);
                release(c, IT_W1 + 7);
                wait_full(c, IT_W2 + 1);
                hprobe(V_HA + 5);
                hfetch(2);
#pragma unroll
                for (int k = 0; k < 8; k++) Hb[k][0] = launder(tagged(Hb[k][0], ltag));
                auto send_b = [&](int k0, int k1) {
#pragma unroll
                    for (int k = k0; k < k1; k++) stv(c.mb + voff(V_HB + k), Hb[k][0], Hb[k][1], Hb[k][2], Hb[k][3]);
                };
                send_b(0, HB0);
                sched_fence(c);
#pragma unroll
                for (int st = 1; st < 6; st++) {
                    if (st == 1) step_b(1, Hb); else if (st < 5) step_a(st, bufa[st > 1 && st < 5 ? st - 2 : 0]); else step_b(st, bufb[0]);
                    wg_wait<1>();
                    release(c, IT_W2 + st - 1);
                    wait_full(c, IT_W2 + st + 1);
                    hcheck(st + 1);
                    if (st == 3) hprobe(V_HB + 7);
                    hfetch(st + 2);
                    if (st == 1) send_b(HB0, HB1);
                    if (st == 2) send_b(HB1, 8);
                    sched_fence(c);
                    if (layer == 1) TL(40 + st);
                }
                order_wait<3>(c);
                wg_wait<0>();
                reg_fence(acc);
                float own[32], par[48];
                rename<48, 32>(par, acc);
                rename<32, 0>(own, acc);
#pragma unroll
                for (int st = 6; st < 8; st++) {
                    if (st == 7) { order_post<3>(c); release(c, IT_W2 + 5); wait_full(c, IT_W2 + 7); hcheck(7); order_wait<4>(c); }
                    wg_fence();
#pragma unroll
                    for (int k = 0; k < 8; k++) wgmma_n96_acc(par, bufb[st - 5][k], mkdesc(c.sb16, slot_off(IT_W2 + st) + k * 1024, 8192, 512, 2));
                    wg_commit();
                }
                order_post<4>(c);
                wait_full(c, IT_W2 + 8);
                auto own_step = [&](int i) {
                    wg_fence();
#pragma unroll
                    for (int k = 0; k < 8; k++) wgmma_n64_acc(own, bufb[1 + i][k], mkdesc(c.sb16, slot_off(IT_W2 + 8) + i * 16384 + k * 1024, 8192, 512, 2));
                    wg_commit();
                };
                own_step(0);
                wg_wait<1>();
                reg_fence(par);
                release(c, IT_W2 + 6);
                release(c, IT_W2 + 7);
                float rem[8];
                uint32_t P[5][4];
                {
                    const bool odd = r & 1;
#pragma unroll
                    for (int u = 0; u < 5; u++)
#pragma unroll
                        for (int i = 0; i < 4; i++) {
                            const int e = 8 * u + 2 * i;
                            if (u < 4) P[u][i] = pack2(par[e], par[e + 1]);
                            else P[u][i] = pack2(odd ? par[e] : par[e + 8], odd ? par[e + 1] : par[e + 9]);
                        }
                    publish(c, P, V_O, 0u);
#pragma unroll
                    for (int i = 0; i < 8; i++) rem[i] = odd ? par[40 + i] : par[32 + i];
                }
                sched_fence(c);
                own_step(1);
                if (layer == 1) TL(47);
                sched_fence(c);
                auto pfetch = [&]() { ld_vecs(P, c.box(r ^ 1), V_O); };
                pfetch();
                unpark_x(c, X);
                wg_wait<0>();
                reg_fence(own);
                release(c, IT_W2 + 8);
#pragma unroll
                for (int u = 0; u < 5; u++)
#pragma unroll
                    for (int i = 0; i < 4; i++) {
                        const float rs = (i & 1) ? rsB : rsA;
                        const int e = 8 * u + 2 * i;
                        xv[e] = fmaf(rs, u < 4 ? own[e & 31] : rem[e & 7], bf_lo(X[u][i]));
                        xv[e + 1] = fmaf(rs, u < 4 ? own[(e + 1) & 31] : rem[(e + 1) & 7], bf_hi(X[u][i]));
                    }
                reg_fence(xv);
                if (layer == 0) wait_full(c, 0); else sched_fence(c);
                check_vecs(c, P, 0u, pfetch);
                TL(8 + layer * 16);
#pragma unroll
                for (int u = 0; u < 5; u++)
#pragma unroll
                    for (int i = 0; i < 4; i++) {
                        const float rs = (i & 1) ? rsB : rsA;
                        const int e = 8 * u + 2 * i;
                        xv[e] = fmaf(rs, bf_lo(P[u][i]), xv[e]);
                        xv[e + 1] = fmaf(rs, bf_hi(P[u][i]), xv[e + 1]);
                    }
                pack_x(X, xv);
                if (layer == 1) break;
                if (DBG_STAGE == 2) store_out(c, X, &tmOut, blk);
                park_x(c, X);
            }
            TL(9 + layer * 16);
        }
        if (DBG_STAGE == 4) store_out(c, X, &tmOut, blk);
        TL(25);
        TLDUMP(64);
        if (warp == 0) reinterpret_cast<unsigned*>(prm.scr + G_EPOCH + role * 128)[c.lane()] = c.eall;
    }
}

typedef CUresult (*EncodeFn)(CUtensorMap*, CUtensorMapDataType, cuuint32_t, void*, const cuuint64_t*, const cuuint64_t*,
                             const cuuint32_t*, const cuuint32_t*, CUtensorMapInterleave, CUtensorMapSwizzle,
                             CUtensorMapL2promotion, CUtensorMapFloatOOBfill);

void encode(EncodeFn fn, CUtensorMap* tm, const void* ptr, int rank, const cuuint64_t* dims, const cuuint64_t* strides,
            const cuuint32_t* box, CUtensorMapSwizzle sw) {
    const cuuint32_t es[3] = {1, 1, 1};
    fn(tm, CU_TENSOR_MAP_DATA_TYPE_BFLOAT16, rank, const_cast<void*>(ptr), dims, strides, box, es, CU_TENSOR_MAP_INTERLEAVE_NONE, sw,
       CU_TENSOR_MAP_L2_PROMOTION_NONE, CU_TENSOR_MAP_FLOAT_OOB_FILL_NONE);
}

__global__ void occupancy_probe_kernel() {}

struct RoleMap { int v[64]; };
RoleMap make_role_map() {
    RoleMap rm;
    for (int i = 0; i < 64; i++) rm.v[i] = ((i & 7) << 3) | (i >> 3);
    cudaFuncSetAttribute(occupancy_probe_kernel, cudaFuncAttributeMaxDynamicSharedMemorySize, SMEM_BYTES);
    cudaFuncSetAttribute(occupancy_probe_kernel, cudaFuncAttributeNonPortableClusterSizeAllowed, 1);
    int N[17] = {0};
    for (int cs = 2; cs <= 16; cs++) {
        cudaLaunchConfig_t cfg = {};
        cfg.gridDim = dim3(cs * 8); cfg.blockDim = dim3(384); cfg.dynamicSmemBytes = SMEM_BYTES;
        cudaLaunchAttribute at[1];
        at[0].id = cudaLaunchAttributeClusterDimension;
        at[0].val.clusterDim.x = cs; at[0].val.clusterDim.y = 1; at[0].val.clusterDim.z = 1;
        cfg.attrs = at; cfg.numAttrs = 1;
        if (cudaOccupancyMaxActiveClusters(&N[cs], occupancy_probe_kernel, &cfg) != cudaSuccess) { cudaGetLastError(); return rm; }
    }
    int ge[10] = {0};
    for (int k = 5; k <= 8; k++) ge[k] = N[2 * k];
    ge[9] = N[9] - ge[5];
    ge[4] = N[8] - ge[8];
    ge[3] = N[6] - ge[6] - ge[9];
    ge[2] = N[4] - ge[4] - ge[6] - ge[8];
    ge[1] = ge[2];
    int total = 0;
    for (int k = 1; k <= 9; k++) { if (ge[k] < 0 || ge[k] > 16 || (k > 1 && ge[k] > ge[k - 1])) return rm; total += ge[k]; }
    const int singles = N[2] - total;
    if (singles < 0 || N[2] < 64) return rm;
    int col[64], cnt[17] = {0}, n = 0;
    for (; n < singles && n < 64; n++) col[n] = 16;
    for (int k = 1; k <= 9; k++)
        for (int j = ge[k] - 1; j >= 0 && n < 64; j--) col[n++] = (cnt[j]++ < 8) ? j : 16;
    if (n != 64) return rm;
    int pos = 0;
    for (int j = 0; j <= 16; j++)
        for (int i = 0; i < 64; i++)
            if (col[i] == j) rm.v[i] = pos++;
    return rm;
}

}

extern "C" void kernel_launch(void* const* d_in, const int* in_sizes, int n_in, void* d_out, int out_size) {
    const __nv_bfloat16* x = (const __nv_bfloat16*)d_in[0];
    const __nv_bfloat16* wqkv = (const __nv_bfloat16*)d_in[1];
    const __nv_bfloat16* wo = (const __nv_bfloat16*)d_in[2];
    const __nv_bfloat16* w1 = (const __nv_bfloat16*)d_in[4];
    const __nv_bfloat16* w2 = (const __nv_bfloat16*)d_in[5];

    void* fnp = nullptr;
    cudaDriverEntryPointQueryResult qr;
    cudaGetDriverEntryPoint("cuTensorMapEncodeTiled", &fnp, cudaEnableDefault, &qr);
    EncodeFn fn = (EncodeFn)fnp;
    CUtensorMap tmQM, tmQR, tmWO, tmW1a, tmW1b, tmW2, tmW2a, tmOut, tmX;
    {
        const cuuint64_t dims[3] = {640, 640, 3}, strides[2] = {DQKV * 2, 640 * 2};
        const cuuint64_t dims2[2] = {DQKV, 640};
        const cuuint32_t bm[2] = {64, 80}, br[3] = {16, 80, 3};
        encode(fn, &tmQM, wqkv, 2, dims2, strides, bm, CU_TENSOR_MAP_SWIZZLE_128B);
        encode(fn, &tmQR, wqkv, 3, dims, strides, br, CU_TENSOR_MAP_SWIZZLE_32B);
    }
    {
        const cuuint64_t dims[2] = {640, 640}, strides[1] = {640 * 2};
        const cuuint32_t box[2] = {32, 80};
        encode(fn, &tmWO, wo, 2, dims, strides, box, CU_TENSOR_MAP_SWIZZLE_64B);
    }
    {
        const cuuint64_t dims[3] = {32, 640, 54}, strides[2] = {DFF * 2, 64};
        const cuuint32_t boxa[3] = {32, 80, 3}, boxb[3] = {32, 80, 4};
        encode(fn, &tmW1a, w1, 3, dims, strides, boxa, CU_TENSOR_MAP_SWIZZLE_64B);
        encode(fn, &tmW1b, w1, 3, dims, strides, boxb, CU_TENSOR_MAP_SWIZZLE_64B);
    }
    {
        const cuuint64_t dims[2] = {640, DFF}, strides[1] = {640 * 2};
        const cuuint32_t box[2] = {32, 128}, boxa[2] = {32, 96};
        encode(fn, &tmW2, w2, 2, dims, strides, box, CU_TENSOR_MAP_SWIZZLE_64B);
        encode(fn, &tmW2a, w2, 2, dims, strides, boxa, CU_TENSOR_MAP_SWIZZLE_64B);
    }
    {
        const cuuint64_t dims[2] = {1280, 1024}, strides[1] = {1280 * 2};
        const cuuint32_t box[2] = {80, 16};
        encode(fn, &tmOut, d_out, 2, dims, strides, box, CU_TENSOR_MAP_SWIZZLE_NONE);
        const cuuint32_t boxx[2] = {80, 64};
        encode(fn, &tmX, x, 2, dims, strides, boxx, CU_TENSOR_MAP_SWIZZLE_NONE);
    }
    cudaFuncSetAttribute(fused_layers_kernel, cudaFuncAttributeMaxDynamicSharedMemorySize, SMEM_LAUNCH);
    const RoleMap rm = make_role_map();
    Params prm;
    void* scr = nullptr;
    cudaGetSymbolAddress(&scr, g_scratch);
    prm.scr = (char*)scr;
    prm.wqkv = wqkv; prm.w1 = w1;
    for (int i = 0; i < 64; i++) prm.role[i] = (uint8_t)rm.v[i];
    fused_layers_kernel<<<128, 384, SMEM_LAUNCH>>>(prm, tmQM, tmQR, tmWO, tmW1a, tmW1b, tmW2, tmW2a, tmOut, tmX);
}
```

```cpp
#include <cuda_runtime.h>
#include <cuda_bf16.h>
#include <cuda.h>
#include <stdint.h>

#define DBG_STAGE 4
#define TLSEL 0
#define WO_B1 2
#define WO_B2 4
#define LCS 2
#define QPAR 0
#define COLPERM 0x76543210u
#define ORDER 0x1b
#define TLW 0
#define CLR_HALO 1
#define CLR_O 0x44332
#define HB0 4
#define HB1 4

namespace {

constexpr int DM = 640, DQKV = 1920, DFF = 1728;
constexpr float LN_EPS = 1e-5f;
constexpr int SPIN_BUDGET = 1 << 20;
constexpr int REG_HELP = 56, REG_CONS = 224;

constexpr int NSLOT = 5, NITEMS_L = 30, NITEMS = 60;
constexpr int IT_WO = 9, IT_W1 = 13, IT_W2 = 21;
__host__ __device__ constexpr int slot_off(int k) { return k % 5 < 4 ? (k % 5) * 40960 : 3 * 40960 + 38912; }
constexpr int RING_BYTES = 3 * 40960 + 2 * 38912;
constexpr int STAGE_OFF = slot_off(3);

constexpr int OFF_XQM = RING_BYTES;
constexpr int OFF_XW1 = OFF_XQM + 3072;
constexpr int OFF_XQR = OFF_XW1 + 3584;
constexpr int XTRA_BYTES = 7424;
constexpr int OFF_PARK = OFF_XQM + XTRA_BYTES;
constexpr int OFF_RK = OFF_PARK + 8 * 2560;
constexpr int BAR_FULL = OFF_RK + 256, BAR_EMPTY = BAR_FULL + 40, BAR_STAGE = BAR_EMPTY + 40, BAR_CS = BAR_STAGE + 8, BAR_ORD = BAR_CS + 16;
constexpr int NORD = 5;
constexpr int BAR_X = BAR_ORD + NORD * 8;
constexpr int SMEM_BYTES = BAR_X + 16;
static_assert(SMEM_BYTES <= 232448 - 512, "smem");

constexpr int V_X = 0, V_O = 5, V_HB = 10, V_HA = 18, V_ST = 24, V_HALO = 25;
constexpr int WBOX = 5 * 512, RBOX = 8 * WBOX, PLANE = 8 * RBOX, BBOX = 9 * PLANE;
__host__ __device__ constexpr int voff(int v) { return v / 5 * PLANE + v % 5 * 512; }
constexpr uint32_t G_CS = 16 * BBOX;
constexpr uint32_t G_EPOCH = G_CS + 8 * 2 * 3 * 5120;
constexpr uint32_t G_BYTES = G_EPOCH + 128 * 128;
__device__ __align__(1024) uint4 g_scratch[G_BYTES / 16];

struct Params {
    char* scr;
    const __nv_bfloat16 *wqkv, *w1;
    int lcs;
    uint8_t role[64];
};

#define TL(slot) do {} while (0)
#define TLH(slot) do {} while (0)
#define TLDUMP(n) do {} while (0)
#define TLINIT
constexpr int SMEM_LAUNCH = SMEM_BYTES;

template <int N> struct IntC { static constexpr int value = N; };
__device__ __forceinline__ uint32_t smem_u32(const void* p) { return (uint32_t)__cvta_generic_to_shared(p); }
__device__ __forceinline__ int launder(int v) { asm volatile("" : "+r"(v)); return v; }
__device__ __forceinline__ bool elect_one() {
    uint32_t p;
    asm volatile("{.reg .pred q; elect.sync _|q, 0xffffffff; selp.u32 %0, 1, 0, q;}" : "=r"(p));
    return p;
}
__device__ __forceinline__ void mbar_init(uint32_t b, int c) { asm volatile("mbarrier.init.shared::cta.b64 [%0], %1;" :: "r"(b), "r"(c) : "memory"); }
__device__ __forceinline__ void mbar_expect(uint32_t b, int bytes) { asm volatile("mbarrier.arrive.expect_tx.shared::cta.b64 _, [%0], %1;" :: "r"(b), "r"(bytes) : "memory"); }
__device__ __forceinline__ void mbar_arrive(uint32_t b) { asm volatile("mbarrier.arrive.shared::cta.b64 _, [%0];" :: "r"(b) : "memory"); }
__device__ __forceinline__ void mbar_arrive_cluster(uint32_t b) { asm volatile("mbarrier.arrive.shared::cluster.b64 _, [%0];" :: "r"(b) : "memory"); }
__device__ __forceinline__ void mbar_wait(uint32_t b, uint32_t parity, int& budget) {
    uint32_t ok;
#pragma unroll 1
    do {
        asm volatile("{.reg .pred p; mbarrier.try_wait.parity.shared::cta.b64 p, [%1], %2; selp.u32 %0, 1, 0, p;}" : "=r"(ok) : "r"(b), "r"(parity) : "memory");
    } while (!ok && --budget >= 0);
}
__device__ __forceinline__ void ldv(uint32_t (&v)[4], const void* p) {
    asm volatile("{.reg .b128 t; ld.relaxed.gpu.global.b128 t, [%4]; mov.b128 {%0,%1,%2,%3}, t;}"
                 : "=r"(v[0]), "=r"(v[1]), "=r"(v[2]), "=r"(v[3]) : "l"(p) : "memory");
}
__device__ __forceinline__ void stv(void* p, uint32_t a, uint32_t b, uint32_t c, uint32_t d) {
    asm volatile("{.reg .b128 t; mov.b128 t, {%0,%1,%2,%3}; st.relaxed.gpu.global.b128 [%4], t;}"
                 :: "r"(a), "r"(b), "r"(c), "r"(d), "l"(p) : "memory");
}
__device__ __forceinline__ uint32_t tagged(uint32_t w, uint32_t tag) { return (w & ~1u) | tag; }
__device__ __forceinline__ uint32_t pack2(float lo, float hi) {
    uint32_t r; asm("cvt.rn.bf16x2.f32 %0, %1, %2;" : "=r"(r) : "f"(hi), "f"(lo)); return r;
}
__device__ __forceinline__ uint32_t pack2_relu(float lo, float hi) {
    uint32_t r; asm("cvt.rn.relu.bf16x2.f32 %0, %1, %2;" : "=r"(r) : "f"(hi), "f"(lo)); return r;
}
__device__ __forceinline__ float bf_lo(uint32_t w) { return __uint_as_float(w << 16); }
__device__ __forceinline__ float bf_hi(uint32_t w) { return __uint_as_float(w & 0xffff0000u); }
__device__ __forceinline__ uint32_t movm(uint32_t a) {
    uint32_t r; asm volatile("movmatrix.sync.aligned.m8n8.trans.b16 %0, %1;" : "=r"(r) : "r"(a)); return r;
}
__device__ __forceinline__ void ldsm4(uint32_t (&v)[4], uint32_t a) {
    asm volatile("ldmatrix.sync.aligned.m8n8.x4.shared.b16 {%0,%1,%2,%3}, [%4];" : "=r"(v[0]), "=r"(v[1]), "=r"(v[2]), "=r"(v[3]) : "r"(a) : "memory");
}
__device__ __forceinline__ void ldsm4t(uint32_t (&v)[4], uint32_t a) {
    asm volatile("ldmatrix.sync.aligned.m8n8.x4.trans.shared.b16 {%0,%1,%2,%3}, [%4];" : "=r"(v[0]), "=r"(v[1]), "=r"(v[2]), "=r"(v[3]) : "r"(a) : "memory");
}
__device__ __forceinline__ void stsm4(uint32_t a, uint32_t v0, uint32_t v1, uint32_t v2, uint32_t v3) {
    asm volatile("stmatrix.sync.aligned.m8n8.x4.shared.b16 [%0], {%1,%2,%3,%4};" :: "r"(a), "r"(v0), "r"(v1), "r"(v2), "r"(v3) : "memory");
}
__device__ __forceinline__ float ex2(float x) { float r; asm("ex2.approx.ftz.f32 %0, %1;" : "=f"(r) : "f"(x)); return r; }
__device__ __forceinline__ float rcp(float x) { float r; asm("rcp.approx.ftz.f32 %0, %1;" : "=f"(r) : "f"(x)); return r; }
__device__ __forceinline__ float rsq(float x) { float r; asm("rsqrt.approx.ftz.f32 %0, %1;" : "=f"(r) : "f"(x)); return r; }
__device__ __forceinline__ void mma_k8_init(float (&d)[4], uint32_t a0, uint32_t a1, uint32_t b0) {
    asm volatile("mma.sync.aligned.m16n8k8.row.col.f32.bf16.bf16.f32 {%0,%1,%2,%3}, {%4,%5}, {%6}, {%7,%7,%7,%7};"
                 : "=f"(d[0]), "=f"(d[1]), "=f"(d[2]), "=f"(d[3]) : "r"(a0), "r"(a1), "r"(b0), "f"(0.f));
}
__device__ __forceinline__ void mma_k16_acc(float (&d)[4], uint32_t a0, uint32_t a1, uint32_t a2, uint32_t a3, uint32_t b0, uint32_t b1) {
    asm volatile("mma.sync.aligned.m16n8k16.row.col.f32.bf16.bf16.f32 {%0,%1,%2,%3}, {%4,%5,%6,%7}, {%8,%9}, {%0,%1,%2,%3};"
                 : "+f"(d[0]), "+f"(d[1]), "+f"(d[2]), "+f"(d[3]) : "r"(a0), "r"(a1), "r"(a2), "r"(a3), "r"(b0), "r"(b1));
}
__device__ __forceinline__ void wg_fence() { asm volatile("wgmma.fence.sync.aligned;" ::: "memory"); }
__device__ __forceinline__ void wg_commit() { asm volatile("wgmma.commit_group.sync.aligned;" ::: "memory"); }
template <int N> __device__ __forceinline__ void wg_wait() { asm volatile("wgmma.wait_group.sync.aligned %0;" :: "n"(N) : "memory"); }
template <int N> __device__ __forceinline__ void reg_fence(float (&d)[N]) {
#pragma unroll
    for (int i = 0; i < N; i++) asm volatile("" : "+f"(d[i]) :: "memory");
}
template <int N, int OFF, int TOT> __device__ __forceinline__ void rename(float (&d)[N], const float (&s)[TOT]) {
#pragma unroll
    for (int i = 0; i < N; i++) asm volatile("mov.f32 %0, %1;" : "=f"(d[i]) : "f"(s[OFF + i]));
}
__device__ __forceinline__ uint64_t mkdesc(uint32_t a16, uint32_t off, uint32_t lbo, uint32_t sbo, int sw) {
    const uint32_t lo = a16 + ((off >> 4) + ((lbo >> 4) << 16));
    const uint32_t hi = (sbo >> 4) | ((uint32_t)sw << 30);
    return ((uint64_t)hi << 32) | lo;
}
__device__ __forceinline__ void tma2d_mc(uint32_t dst, const CUtensorMap* tm, int c0, int c1, uint32_t bar, uint16_t mask) {
    asm volatile("cp.async.bulk.tensor.2d.shared::cluster.global.mbarrier::complete_tx::bytes.multicast::cluster [%0], [%1, {%3, %4}], [%2], %5;"
                 :: "r"(dst), "l"(tm), "r"(bar), "r"(c0), "r"(c1), "h"(mask) : "memory");
}
__device__ __forceinline__ void tma2d(uint32_t dst, const CUtensorMap* tm, int c0, int c1, uint32_t bar) {
    asm volatile("cp.async.bulk.tensor.2d.shared::cluster.global.mbarrier::complete_tx::bytes [%0], [%1, {%3, %4}], [%2];"
                 :: "r"(dst), "l"(tm), "r"(bar), "r"(c0), "r"(c1) : "memory");
}
__device__ __forceinline__ void tma3d_mc(uint32_t dst, const CUtensorMap* tm, int c0, int c1, int c2, uint32_t bar, uint16_t mask) {
    asm volatile("cp.async.bulk.tensor.3d.shared::cluster.global.mbarrier::complete_tx::bytes.multicast::cluster [%0], [%1, {%3, %4, %5}], [%2], %6;"
                 :: "r"(dst), "l"(tm), "r"(bar), "r"(c0), "r"(c1), "r"(c2), "h"(mask) : "memory");
}
__device__ __forceinline__ void prefetch_map(const CUtensorMap* tm) { asm volatile("prefetch.tensormap [%0];" :: "l"(tm) : "memory"); }

__device__ __forceinline__ void wgmma_n192_acc(float (&d)[96], const uint32_t (&a)[4], uint64_t db) {
    asm volatile("{.reg .pred p; setp.eq.b32 p, 0, 0;\n"
        "wgmma.mma_async.sync.aligned.m64n192k16.f32.bf16.bf16 {"
        "%0, %1, %2, %3, %4, %5, %6, %7, %8, %9, %10, %11, %12, %13, %14, %15, %16, %17, %18, %19, %20, %21, %22, %23, "
        "%24, %25, %26, %27, %28, %29, %30, %31, %32, %33, %34, %35, %36, %37, %38, %39, %40, %41, %42, %43, %44, %45, %46, %47, "
        "%48, %49, %50, %51, %52, %53, %54, %55, %56, %57, %58, %59, %60, %61, %62, %63, %64, %65, %66, %67, %68, %69, %70, %71, "
        "%72, %73, %74, %75, %76, %77, %78, %79, %80, %81, %82, %83, %84, %85, %86, %87, %88, %89, %90, %91, %92, %93, %94, %95"
        "}, {%96, %97, %98, %99}, %100, p, 1, 1, 1;}\n"
        : "+f"(d[0]), "+f"(d[1]), "+f"(d[2]), "+f"(d[3]), "+f"(d[4]), "+f"(d[5]), "+f"(d[6]), "+f"(d[7]), "+f"(d[8]), "+f"(d[9]), "+f"(d[10]), "+f"(d[11]),
          "+f"(d[12]), "+f"(d[13]), "+f"(d[14]), "+f"(d[15]), "+f"(d[16]), "+f"(d[17]), "+f"(d[18]), "+f"(d[19]), "+f"(d[20]), "+f"(d[21]), "+f"(d[22]), "+f"(d[23]),
          "+f"(d[24]), "+f"(d[25]), "+f"(d[26]), "+f"(d[27]), "+f"(d[28]), "+f"(d[29]), "+f"(d[30]), "+f"(d[31]), "+f"(d[32]), "+f"(d[33]), "+f"(d[34]), "+f"(d[35]),
          "+f"(d[36]), "+f"(d[37]), "+f"(d[38]), "+f"(d[39]), "+f"(d[40]), "+f"(d[41]), "+f"(d[42]), "+f"(d[43]), "+f"(d[44]), "+f"(d[45]), "+f"(d[46]), "+f"(d[47]),
          "+f"(d[48]), "+f"(d[49]), "+f"(d[50]), "+f"(d[51]), "+f"(d[52]), "+f"(d[53]), "+f"(d[54]), "+f"(d[55]), "+f"(d[56]), "+f"(d[57]), "+f"(d[58]), "+f"(d[59]),
          "+f"(d[60]), "+f"(d[61]), "+f"(d[62]), "+f"(d[63]), "+f"(d[64]), "+f"(d[65]), "+f"(d[66]), "+f"(d[67]), "+f"(d[68]), "+f"(d[69]), "+f"(d[70]), "+f"(d[71]),
          "+f"(d[72]), "+f"(d[73]), "+f"(d[74]), "+f"(d[75]), "+f"(d[76]), "+f"(d[77]), "+f"(d[78]), "+f"(d[79]), "+f"(d[80]), "+f"(d[81]), "+f"(d[82]), "+f"(d[83]),
          "+f"(d[84]), "+f"(d[85]), "+f"(d[86]), "+f"(d[87]), "+f"(d[88]), "+f"(d[89]), "+f"(d[90]), "+f"(d[91]), "+f"(d[92]), "+f"(d[93]), "+f"(d[94]), "+f"(d[95])
        : "r"(a[0]), "r"(a[1]), "r"(a[2]), "r"(a[3]), "l"(db));
}
__device__ __forceinline__ void wgmma_n192_init(float (&d)[96], const uint32_t (&a)[4], uint64_t db) {
    asm volatile("{.reg .pred p; setp.ne.b32 p, 0, 0;\n"
        "wgmma.mma_async.sync.aligned.m64n192k16.f32.bf16.bf16 {"
        "%0, %1, %2, %3, %4, %5, %6, %7, %8, %9, %10, %11, %12, %13, %14, %15, %16, %17, %18, %19, %20, %21, %22, %23, "
        "%24, %25, %26, %27, %28, %29, %30, %31, %32, %33, %34, %35, %36, %37, %38, %39, %40, %41, %42, %43, %44, %45, %46, %47, "
        "%48, %49, %50, %51, %52, %53, %54, %55, %56, %57, %58, %59, %60, %61, %62, %63, %64, %65, %66, %67, %68, %69, %70, %71, "
        "%72, %73, %74, %75, %76, %77, %78, %79, %80, %81, %82, %83, %84, %85, %86, %87, %88, %89, %90, %91, %92, %93, %94, %95"
        "}, {%96, %97, %98, %99}, %100, p, 1, 1, 1;}\n"
        : "=f"(d[0]), "=f"(d[1]), "=f"(d[2]), "=f"(d[3]), "=f"(d[4]), "=f"(d[5]), "=f"(d[6]), "=f"(d[7]), "=f"(d[8]), "=f"(d[9]), "=f"(d[10]), "=f"(d[11]),
          "=f"(d[12]), "=f"(d[13]), "=f"(d[14]), "=f"(d[15]), "=f"(d[16]), "=f"(d[17]), "=f"(d[18]), "=f"(d[19]), "=f"(d[20]), "=f"(d[21]), "=f"(d[22]), "=f"(d[23]),
          "=f"(d[24]), "=f"(d[25]), "=f"(d[26]), "=f"(d[27]), "=f"(d[28]), "=f"(d[29]), "=f"(d[30]), "=f"(d[31]), "=f"(d[32]), "=f"(d[33]), "=f"(d[34]), "=f"(d[35]),
          "=f"(d[36]), "=f"(d[37]), "=f"(d[38]), "=f"(d[39]), "=f"(d[40]), "=f"(d[41]), "=f"(d[42]), "=f"(d[43]), "=f"(d[44]), "=f"(d[45]), "=f"(d[46]), "=f"(d[47]),
          "=f"(d[48]), "=f"(d[49]), "=f"(d[50]), "=f"(d[51]), "=f"(d[52]), "=f"(d[53]), "=f"(d[54]), "=f"(d[55]), "=f"(d[56]), "=f"(d[57]), "=f"(d[58]), "=f"(d[59]),
          "=f"(d[60]), "=f"(d[61]), "=f"(d[62]), "=f"(d[63]), "=f"(d[64]), "=f"(d[65]), "=f"(d[66]), "=f"(d[67]), "=f"(d[68]), "=f"(d[69]), "=f"(d[70]), "=f"(d[71]),
          "=f"(d[72]), "=f"(d[73]), "=f"(d[74]), "=f"(d[75]), "=f"(d[76]), "=f"(d[77]), "=f"(d[78]), "=f"(d[79]), "=f"(d[80]), "=f"(d[81]), "=f"(d[82]), "=f"(d[83]),
          "=f"(d[84]), "=f"(d[85]), "=f"(d[86]), "=f"(d[87]), "=f"(d[88]), "=f"(d[89]), "=f"(d[90]), "=f"(d[91]), "=f"(d[92]), "=f"(d[93]), "=f"(d[94]), "=f"(d[95])
        : "r"(a[0]), "r"(a[1]), "r"(a[2]), "r"(a[3]), "l"(db));
}
__device__ __forceinline__ void wgmma_n48_acc(float (&d)[24], const uint32_t (&a)[4], uint64_t db) {
    asm volatile("{.reg .pred p; setp.eq.b32 p, 0, 0;\n"
        "wgmma.mma_async.sync.aligned.m64n48k16.f32.bf16.bf16 {"
        "%0, %1, %2, %3, %4, %5, %6, %7, %8, %9, %10, %11, %12, %13, %14, %15, %16, %17, %18, %19, %20, %21, %22, %23"
        "}, {%24, %25, %26, %27}, %28, p, 1, 1, 1;}\n"
        : "+f"(d[0]), "+f"(d[1]), "+f"(d[2]), "+f"(d[3]), "+f"(d[4]), "+f"(d[5]), "+f"(d[6]), "+f"(d[7]), "+f"(d[8]), "+f"(d[9]), "+f"(d[10]), "+f"(d[11]),
          "+f"(d[12]), "+f"(d[13]), "+f"(d[14]), "+f"(d[15]), "+f"(d[16]), "+f"(d[17]), "+f"(d[18]), "+f"(d[19]), "+f"(d[20]), "+f"(d[21]), "+f"(d[22]), "+f"(d[23])
        : "r"(a[0]), "r"(a[1]), "r"(a[2]), "r"(a[3]), "l"(db));
}
__device__ __forceinline__ void wgmma_n48_init(float (&d)[24], const uint32_t (&a)[4], uint64_t db) {
    asm volatile("{.reg .pred p; setp.ne.b32 p, 0, 0;\n"
        "wgmma.mma_async.sync.aligned.m64n48k16.f32.bf16.bf16 {"
        "%0, %1, %2, %3, %4, %5, %6, %7, %8, %9, %10, %11, %12, %13, %14, %15, %16, %17, %18, %19, %20, %21, %22, %23"
        "}, {%24, %25, %26, %27}, %28, p, 1, 1, 1;}\n"
        : "=f"(d[0]), "=f"(d[1]), "=f"(d[2]), "=f"(d[3]), "=f"(d[4]), "=f"(d[5]), "=f"(d[6]), "=f"(d[7]), "=f"(d[8]), "=f"(d[9]), "=f"(d[10]), "=f"(d[11]),
          "=f"(d[12]), "=f"(d[13]), "=f"(d[14]), "=f"(d[15]), "=f"(d[16]), "=f"(d[17]), "=f"(d[18]), "=f"(d[19]), "=f"(d[20]), "=f"(d[21]), "=f"(d[22]), "=f"(d[23])
        : "r"(a[0]), "r"(a[1]), "r"(a[2]), "r"(a[3]), "l"(db));
}
__device__ __forceinline__ void wgmma_n224_acc(float (&d)[112], const uint32_t (&a)[4], uint64_t db) {
    asm volatile("{.reg .pred p; setp.eq.b32 p, 0, 0;\n"
        "wgmma.mma_async.sync.aligned.m64n224k16.f32.bf16.bf16 {"
        "%0, %1, %2, %3, %4, %5, %6, %7, %8, %9, %10, %11, %12, %13, %14, %15, %16, %17, %18, %19, %20, %21, %22, %23, "
        "%24, %25, %26, %27, %28, %29, %30, %31, %32, %33, %34, %35, %36, %37, %38, %39, %40, %41, %42, %43, %44, %45, %46, %47, "
        "%48, %49, %50, %51, %52, %53, %54, %55, %56, %57, %58, %59, %60, %61, %62, %63, %64, %65, %66, %67, %68, %69, %70, %71, "
        "%72, %73, %74, %75, %76, %77, %78, %79, %80, %81, %82, %83, %84, %85, %86, %87, %88, %89, %90, %91, %92, %93, %94, %95, "
        "%96, %97, %98, %99, %100, %101, %102, %103, %104, %105, %106, %107, %108, %109, %110, %111"
        "}, {%112, %113, %114, %115}, %116, p, 1, 1, 1;}\n"
        : "+f"(d[0]), "+f"(d[1]), "+f"(d[2]), "+f"(d[3]), "+f"(d[4]), "+f"(d[5]), "+f"(d[6]), "+f"(d[7]), "+f"(d[8]), "+f"(d[9]), "+f"(d[10]), "+f"(d[11]),
          "+f"(d[12]), "+f"(d[13]), "+f"(d[14]), "+f"(d[15]), "+f"(d[16]), "+f"(d[17]), "+f"(d[18]), "+f"(d[19]), "+f"(d[20]), "+f"(d[21]), "+f"(d[22]), "+f"(d[23]),
          "+f"(d[24]), "+f"(d[25]), "+f"(d[26]), "+f"(d[27]), "+f"(d[28]), "+f"(d[29]), "+f"(d[30]), "+f"(d[31]), "+f"(d[32]), "+f"(d[33]), "+f"(d[34]), "+f"(d[35]),
          "+f"(d[36]), "+f"(d[37]), "+f"(d[38]), "+f"(d[39]), "+f"(d[40]), "+f"(d[41]), "+f"(d[42]), "+f"(d[43]), "+f"(d[44]), "+f"(d[45]), "+f"(d[46]), "+f"(d[47]),
          "+f"(d[48]), "+f"(d[49]), "+f"(d[50]), "+f"(d[51]), "+f"(d[52]), "+f"(d[53]), "+f"(d[54]), "+f"(d[55]), "+f"(d[56]), "+f"(d[57]), "+f"(d[58]), "+f"(d[59]),
          "+f"(d[60]), "+f"(d[61]), "+f"(d[62]), "+f"(d[63]), "+f"(d[64]), "+f"(d[65]), "+f"(d[66]), "+f"(d[67]), "+f"(d[68]), "+f"(d[69]), "+f"(d[70]), "+f"(d[71]),
          "+f"(d[72]), "+f"(d[73]), "+f"(d[74]), "+f"(d[75]), "+f"(d[76]), "+f"(d[77]), "+f"(d[78]), "+f"(d[79]), "+f"(d[80]), "+f"(d[81]), "+f"(d[82]), "+f"(d[83]),
          "+f"(d[84]), "+f"(d[85]), "+f"(d[86]), "+f"(d[87]), "+f"(d[88]), "+f"(d[89]), "+f"(d[90]), "+f"(d[91]), "+f"(d[92]), "+f"(d[93]), "+f"(d[94]), "+f"(d[95]),
          "+f"(d[96]), "+f"(d[97]), "+f"(d[98]), "+f"(d[99]), "+f"(d[100]), "+f"(d[101]), "+f"(d[102]), "+f"(d[103]), "+f"(d[104]), "+f"(d[105]), "+f"(d[106]), "+f"(d[107]),
          "+f"(d[108]), "+f"(d[109]), "+f"(d[110]), "+f"(d[111])
        : "r"(a[0]), "r"(a[1]), "r"(a[2]), "r"(a[3]), "l"(db));
}
__device__ __forceinline__ void wgmma_n224_init(float (&d)[112], const uint32_t (&a)[4], uint64_t db) {
    asm volatile("{.reg .pred p; setp.ne.b32 p, 0, 0;\n"
        "wgmma.mma_async.sync.aligned.m64n224k16.f32.bf16.bf16 {"
        "%0, %1, %2, %3, %4, %5, %6, %7, %8, %9, %10, %11, %12, %13, %14, %15, %16, %17, %18, %19, %20, %21, %22, %23, "
        "%24, %25, %26, %27, %28, %29, %30, %31, %32, %33, %34, %35, %36, %37, %38, %39, %40, %41, %42, %43, %44, %45, %46, %47, "
        "%48, %49, %50, %51, %52, %53, %54, %55, %56, %57, %58, %59, %60, %61, %62, %63, %64, %65, %66, %67, %68, %69, %70, %71, "
        "%72, %73, %74, %75, %76, %77, %78, %79, %80, %81, %82, %83, %84, %85, %86, %87, %88, %89, %90, %91, %92, %93, %94, %95, "
        "%96, %97, %98, %99, %100, %101, %102, %103, %104, %105, %106, %107, %108, %109, %110, %111"
        "}, {%112, %113, %114, %115}, %116, p, 1, 1, 1;}\n"
        : "=f"(d[0]), "=f"(d[1]), "=f"(d[2]), "=f"(d[3]), "=f"(d[4]), "=f"(d[5]), "=f"(d[6]), "=f"(d[7]), "=f"(d[8]), "=f"(d[9]), "=f"(d[10]), "=f"(d[11]),
          "=f"(d[12]), "=f"(d[13]), "=f"(d[14]), "=f"(d[15]), "=f"(d[16]), "=f"(d[17]), "=f"(d[18]), "=f"(d[19]), "=f"(d[20]), "=f"(d[21]), "=f"(d[22]), "=f"(d[23]),
          "=f"(d[24]), "=f"(d[25]), "=f"(d[26]), "=f"(d[27]), "=f"(d[28]), "=f"(d[29]), "=f"(d[30]), "=f"(d[31]), "=f"(d[32]), "=f"(d[33]), "=f"(d[34]), "=f"(d[35]),
          "=f"(d[36]), "=f"(d[37]), "=f"(d[38]), "=f"(d[39]), "=f"(d[40]), "=f"(d[41]), "=f"(d[42]), "=f"(d[43]), "=f"(d[44]), "=f"(d[45]), "=f"(d[46]), "=f"(d[47]),
          "=f"(d[48]), "=f"(d[49]), "=f"(d[50]), "=f"(d[51]), "=f"(d[52]), "=f"(d[53]), "=f"(d[54]), "=f"(d[55]), "=f"(d[56]), "=f"(d[57]), "=f"(d[58]), "=f"(d[59]),
          "=f"(d[60]), "=f"(d[61]), "=f"(d[62]), "=f"(d[63]), "=f"(d[64]), "=f"(d[65]), "=f"(d[66]), "=f"(d[67]), "=f"(d[68]), "=f"(d[69]), "=f"(d[70]), "=f"(d[71]),
          "=f"(d[72]), "=f"(d[73]), "=f"(d[74]), "=f"(d[75]), "=f"(d[76]), "=f"(d[77]), "=f"(d[78]), "=f"(d[79]), "=f"(d[80]), "=f"(d[81]), "=f"(d[82]), "=f"(d[83]),
          "=f"(d[84]), "=f"(d[85]), "=f"(d[86]), "=f"(d[87]), "=f"(d[88]), "=f"(d[89]), "=f"(d[90]), "=f"(d[91]), "=f"(d[92]), "=f"(d[93]), "=f"(d[94]), "=f"(d[95]),
          "=f"(d[96]), "=f"(d[97]), "=f"(d[98]), "=f"(d[99]), "=f"(d[100]), "=f"(d[101]), "=f"(d[102]), "=f"(d[103]), "=f"(d[104]), "=f"(d[105]), "=f"(d[106]), "=f"(d[107]),
          "=f"(d[108]), "=f"(d[109]), "=f"(d[110]), "=f"(d[111])
        : "r"(a[0]), "r"(a[1]), "r"(a[2]), "r"(a[3]), "l"(db));
}
__device__ __forceinline__ void wgmma_n80_acc(float (&d)[40], const uint32_t (&a)[4], uint64_t db) {
    asm volatile("{.reg .pred p; setp.eq.b32 p, 0, 0;\n"
        "wgmma.mma_async.sync.aligned.m64n80k16.f32.bf16.bf16 {"
        "%0, %1, %2, %3, %4, %5, %6, %7, %8, %9, %10, %11, %12, %13, %14, %15, %16, %17, %18, %19, %20, %21, %22, %23, "
        "%24, %25, %26, %27, %28, %29, %30, %31, %32, %33, %34, %35, %36, %37, %38, %39"
        "}, {%40, %41, %42, %43}, %44, p, 1, 1, 1;}\n"
        : "+f"(d[0]), "+f"(d[1]), "+f"(d[2]), "+f"(d[3]), "+f"(d[4]), "+f"(d[5]), "+f"(d[6]), "+f"(d[7]), "+f"(d[8]), "+f"(d[9]), "+f"(d[10]), "+f"(d[11]),
          "+f"(d[12]), "+f"(d[13]), "+f"(d[14]), "+f"(d[15]), "+f"(d[16]), "+f"(d[17]), "+f"(d[18]), "+f"(d[19]), "+f"(d[20]), "+f"(d[21]), "+f"(d[22]), "+f"(d[23]),
          "+f"(d[24]), "+f"(d[25]), "+f"(d[26]), "+f"(d[27]), "+f"(d[28]), "+f"(d[29]), "+f"(d[30]), "+f"(d[31]), "+f"(d[32]), "+f"(d[33]), "+f"(d[34]), "+f"(d[35]),
          "+f"(d[36]), "+f"(d[37]), "+f"(d[38]), "+f"(d[39])
        : "r"(a[0]), "r"(a[1]), "r"(a[2]), "r"(a[3]), "l"(db));
}
__device__ __forceinline__ void wgmma_n160_acc(float (&d)[80], const uint32_t (&a)[4], uint64_t db) {
    asm volatile("{.reg .pred p; setp.eq.b32 p, 0, 0;\n"
        "wgmma.mma_async.sync.aligned.m64n160k16.f32.bf16.bf16 {"
        "%0, %1, %2, %3, %4, %5, %6, %7, %8, %9, %10, %11, %12, %13, %14, %15, %16, %17, %18, %19, %20, %21, %22, %23, "
        "%24, %25, %26, %27, %28, %29, %30, %31, %32, %33, %34, %35, %36, %37, %38, %39, %40, %41, %42, %43, %44, %45, %46, %47, "
        "%48, %49, %50, %51, %52, %53, %54, %55, %56, %57, %58, %59, %60, %61, %62, %63, %64, %65, %66, %67, %68, %69, %70, %71, "
        "%72, %73, %74, %75, %76, %77, %78, %79"
        "}, {%80, %81, %82, %83}, %84, p, 1, 1, 1;}\n"
        : "+f"(d[0]), "+f"(d[1]), "+f"(d[2]), "+f"(d[3]), "+f"(d[4]), "+f"(d[5]), "+f"(d[6]), "+f"(d[7]), "+f"(d[8]), "+f"(d[9]), "+f"(d[10]), "+f"(d[11]),
          "+f"(d[12]), "+f"(d[13]), "+f"(d[14]), "+f"(d[15]), "+f"(d[16]), "+f"(d[17]), "+f"(d[18]), "+f"(d[19]), "+f"(d[20]), "+f"(d[21]), "+f"(d[22]), "+f"(d[23]),
          "+f"(d[24]), "+f"(d[25]), "+f"(d[26]), "+f"(d[27]), "+f"(d[28]), "+f"(d[29]), "+f"(d[30]), "+f"(d[31]), "+f"(d[32]), "+f"(d[33]), "+f"(d[34]), "+f"(d[35]),
          "+f"(d[36]), "+f"(d[37]), "+f"(d[38]), "+f"(d[39]), "+f"(d[40]), "+f"(d[41]), "+f"(d[42]), "+f"(d[43]), "+f"(d[44]), "+f"(d[45]), "+f"(d[46]), "+f"(d[47]),
          "+f"(d[48]), "+f"(d[49]), "+f"(d[50]), "+f"(d[51]), "+f"(d[52]), "+f"(d[53]), "+f"(d[54]), "+f"(d[55]), "+f"(d[56]), "+f"(d[57]), "+f"(d[58]), "+f"(d[59]),
          "+f"(d[60]), "+f"(d[61]), "+f"(d[62]), "+f"(d[63]), "+f"(d[64]), "+f"(d[65]), "+f"(d[66]), "+f"(d[67]), "+f"(d[68]), "+f"(d[69]), "+f"(d[70]), "+f"(d[71]),
          "+f"(d[72]), "+f"(d[73]), "+f"(d[74]), "+f"(d[75]), "+f"(d[76]), "+f"(d[77]), "+f"(d[78]), "+f"(d[79])
        : "r"(a[0]), "r"(a[1]), "r"(a[2]), "r"(a[3]), "l"(db));
}
__device__ __forceinline__ void wgmma_n160_init(float (&d)[80], const uint32_t (&a)[4], uint64_t db) {
    asm volatile("{.reg .pred p; setp.ne.b32 p, 0, 0;\n"
        "wgmma.mma_async.sync.aligned.m64n160k16.f32.bf16.bf16 {"
        "%0, %1, %2, %3, %4, %5, %6, %7, %8, %9, %10, %11, %12, %13, %14, %15, %16, %17, %18, %19, %20, %21, %22, %23, "
        "%24, %25, %26, %27, %28, %29, %30, %31, %32, %33, %34, %35, %36, %37, %38, %39, %40, %41, %42, %43, %44, %45, %46, %47, "
        "%48, %49, %50, %51, %52, %53, %54, %55, %56, %57, %58, %59, %60, %61, %62, %63, %64, %65, %66, %67, %68, %69, %70, %71, "
        "%72, %73, %74, %75, %76, %77, %78, %79"
        "}, {%80, %81, %82, %83}, %84, p, 1, 1, 1;}\n"
        : "=f"(d[0]), "=f"(d[1]), "=f"(d[2]), "=f"(d[3]), "=f"(d[4]), "=f"(d[5]), "=f"(d[6]), "=f"(d[7]), "=f"(d[8]), "=f"(d[9]), "=f"(d[10]), "=f"(d[11]),
          "=f"(d[12]), "=f"(d[13]), "=f"(d[14]), "=f"(d[15]), "=f"(d[16]), "=f"(d[17]), "=f"(d[18]), "=f"(d[19]), "=f"(d[20]), "=f"(d[21]), "=f"(d[22]), "=f"(d[23]),
          "=f"(d[24]), "=f"(d[25]), "=f"(d[26]), "=f"(d[27]), "=f"(d[28]), "=f"(d[29]), "=f"(d[30]), "=f"(d[31]), "=f"(d[32]), "=f"(d[33]), "=f"(d[34]), "=f"(d[35]),
          "=f"(d[36]), "=f"(d[37]), "=f"(d[38]), "=f"(d[39]), "=f"(d[40]), "=f"(d[41]), "=f"(d[42]), "=f"(d[43]), "=f"(d[44]), "=f"(d[45]), "=f"(d[46]), "=f"(d[47]),
          "=f"(d[48]), "=f"(d[49]), "=f"(d[50]), "=f"(d[51]), "=f"(d[52]), "=f"(d[53]), "=f"(d[54]), "=f"(d[55]), "=f"(d[56]), "=f"(d[57]), "=f"(d[58]), "=f"(d[59]),
          "=f"(d[60]), "=f"(d[61]), "=f"(d[62]), "=f"(d[63]), "=f"(d[64]), "=f"(d[65]), "=f"(d[66]), "=f"(d[67]), "=f"(d[68]), "=f"(d[69]), "=f"(d[70]), "=f"(d[71]),
          "=f"(d[72]), "=f"(d[73]), "=f"(d[74]), "=f"(d[75]), "=f"(d[76]), "=f"(d[77]), "=f"(d[78]), "=f"(d[79])
        : "r"(a[0]), "r"(a[1]), "r"(a[2]), "r"(a[3]), "l"(db));
}
__device__ __forceinline__ void wgmma_n128_acc(float (&d)[64], const uint32_t (&a)[4], uint64_t db) {
    asm volatile("{.reg .pred p; setp.eq.b32 p, 0, 0;\n"
        "wgmma.mma_async.sync.aligned.m64n128k16.f32.bf16.bf16 {"
        "%0, %1, %2, %3, %4, %5, %6, %7, %8, %9, %10, %11, %12, %13, %14, %15, %16, %17, %18, %19, %20, %21, %22, %23, "
        "%24, %25, %26, %27, %28, %29, %30, %31, %32, %33, %34, %35, %36, %37, %38, %39, %40, %41, %42, %43, %44, %45, %46, %47, "
        "%48, %49, %50, %51, %52, %53, %54, %55, %56, %57, %58, %59, %60, %61, %62, %63"
        "}, {%64, %65, %66, %67}, %68, p, 1, 1, 1;}\n"
        : "+f"(d[0]), "+f"(d[1]), "+f"(d[2]), "+f"(d[3]), "+f"(d[4]), "+f"(d[5]), "+f"(d[6]), "+f"(d[7]), "+f"(d[8]), "+f"(d[9]), "+f"(d[10]), "+f"(d[11]),
          "+f"(d[12]), "+f"(d[13]), "+f"(d[14]), "+f"(d[15]), "+f"(d[16]), "+f"(d[17]), "+f"(d[18]), "+f"(d[19]), "+f"(d[20]), "+f"(d[21]), "+f"(d[22]), "+f"(d[23]),
          "+f"(d[24]), "+f"(d[25]), "+f"(d[26]), "+f"(d[27]), "+f"(d[28]), "+f"(d[29]), "+f"(d[30]), "+f"(d[31]), "+f"(d[32]), "+f"(d[33]), "+f"(d[34]), "+f"(d[35]),
          "+f"(d[36]), "+f"(d[37]), "+f"(d[38]), "+f"(d[39]), "+f"(d[40]), "+f"(d[41]), "+f"(d[42]), "+f"(d[43]), "+f"(d[44]), "+f"(d[45]), "+f"(d[46]), "+f"(d[47]),
          "+f"(d[48]), "+f"(d[49]), "+f"(d[50]), "+f"(d[51]), "+f"(d[52]), "+f"(d[53]), "+f"(d[54]), "+f"(d[55]), "+f"(d[56]), "+f"(d[57]), "+f"(d[58]), "+f"(d[59]),
          "+f"(d[60]), "+f"(d[61]), "+f"(d[62]), "+f"(d[63])
        : "r"(a[0]), "r"(a[1]), "r"(a[2]), "r"(a[3]), "l"(db));
}
__device__ __forceinline__ void wgmma_n96_acc(float (&d)[48], const uint32_t (&a)[4], uint64_t db) {
    asm volatile("{.reg .pred p; setp.eq.b32 p, 0, 0;\n"
        "wgmma.mma_async.sync.aligned.m64n96k16.f32.bf16.bf16 {"
        "%0, %1, %2, %3, %4, %5, %6, %7, %8, %9, %10, %11, %12, %13, %14, %15, %16, %17, %18, %19, %20, %21, %22, %23, "
        "%24, %25, %26, %27, %28, %29, %30, %31, %32, %33, %34, %35, %36, %37, %38, %39, %40, %41, %42, %43, %44, %45, %46, %47"
        "}, {%48, %49, %50, %51}, %52, p, 1, 1, 1;}\n"
        : "+f"(d[0]), "+f"(d[1]), "+f"(d[2]), "+f"(d[3]), "+f"(d[4]), "+f"(d[5]), "+f"(d[6]), "+f"(d[7]), "+f"(d[8]), "+f"(d[9]), "+f"(d[10]), "+f"(d[11]),
          "+f"(d[12]), "+f"(d[13]), "+f"(d[14]), "+f"(d[15]), "+f"(d[16]), "+f"(d[17]), "+f"(d[18]), "+f"(d[19]), "+f"(d[20]), "+f"(d[21]), "+f"(d[22]), "+f"(d[23]),
          "+f"(d[24]), "+f"(d[25]), "+f"(d[26]), "+f"(d[27]), "+f"(d[28]), "+f"(d[29]), "+f"(d[30]), "+f"(d[31]), "+f"(d[32]), "+f"(d[33]), "+f"(d[34]), "+f"(d[35]),
          "+f"(d[36]), "+f"(d[37]), "+f"(d[38]), "+f"(d[39]), "+f"(d[40]), "+f"(d[41]), "+f"(d[42]), "+f"(d[43]), "+f"(d[44]), "+f"(d[45]), "+f"(d[46]), "+f"(d[47])
        : "r"(a[0]), "r"(a[1]), "r"(a[2]), "r"(a[3]), "l"(db));
}
__device__ __forceinline__ void wgmma_n64_acc(float (&d)[32], const uint32_t (&a)[4], uint64_t db) {
    asm volatile("{.reg .pred p; setp.eq.b32 p, 0, 0;\n"
        "wgmma.mma_async.sync.aligned.m64n64k16.f32.bf16.bf16 {"
        "%0, %1, %2, %3, %4, %5, %6, %7, %8, %9, %10, %11, %12, %13, %14, %15, %16, %17, %18, %19, %20, %21, %22, %23, "
        "%24, %25, %26, %27, %28, %29, %30, %31"
        "}, {%32, %33, %34, %35}, %36, p, 1, 1, 1;}\n"
        : "+f"(d[0]), "+f"(d[1]), "+f"(d[2]), "+f"(d[3]), "+f"(d[4]), "+f"(d[5]), "+f"(d[6]), "+f"(d[7]), "+f"(d[8]), "+f"(d[9]), "+f"(d[10]), "+f"(d[11]),
          "+f"(d[12]), "+f"(d[13]), "+f"(d[14]), "+f"(d[15]), "+f"(d[16]), "+f"(d[17]), "+f"(d[18]), "+f"(d[19]), "+f"(d[20]), "+f"(d[21]), "+f"(d[22]), "+f"(d[23]),
          "+f"(d[24]), "+f"(d[25]), "+f"(d[26]), "+f"(d[27]), "+f"(d[28]), "+f"(d[29]), "+f"(d[30]), "+f"(d[31])
        : "r"(a[0]), "r"(a[1]), "r"(a[2]), "r"(a[3]), "l"(db));
}

__device__ __forceinline__ int slice_at(int t, int r) { return t < 2 ? r ^ t : (t - 2) + ((t - 2) >= (r & 6) ? 2 : 0); }
__device__ __forceinline__ int main_col(int j) { return 80 * j + 16 * (j & 1); }
__device__ __forceinline__ int rem_col(int j) { return 80 * j + 64 - 64 * (j & 1); }
__device__ __forceinline__ int kstep(int odd, int u) { return u < 4 ? odd + u : 4 - 4 * odd; }
__device__ __forceinline__ int hsrc_at(int t, int r) {
    if (t < 2) return r;
    const int i = t < 5 ? t - 2 : t - 5;
    return 2 * (i + (i >= (r >> 1) ? 1 : 0)) + (r & 1);
}
__device__ __forceinline__ constexpr bool hpartB(int t) { return t == 1 || t >= 5; }

template <int NV> __device__ __forceinline__ bool bad_vecs(const uint32_t (&v)[NV][4], uint32_t tag) {
    uint32_t bad = 0;
#pragma unroll
    for (int u = 0; u < NV; u += 2) {
        if (u + 1 < NV) {
            uint32_t x;
            asm("lop3.b32 %0, %1, %2, %3, 0x7e;" : "=r"(x) : "r"(v[u][0]), "r"(v[u + 1][0]), "r"(tag));
            if (u == 0) bad = x; else asm("or.b32 %0, %0, %1;" : "+r"(bad) : "r"(x));
        } else {
            asm("lop3.b32 %0, %1, %2, %0, 0xbe;" : "+r"(bad) : "r"(v[u][0]), "r"(tag));
        }
    }
    return __any_sync(0xffffffffu, bad & 1);
}

struct Ctx {
    uint32_t sb, sb16;
    uint32_t rel_addr;
    char* mb;
    int r, warp, layer;
    int budget;
    uint32_t eall;
    __device__ __forceinline__ uint32_t lane16() const { return launder((uint32_t)(size_t)mb) & 511; }
    __device__ __forceinline__ int lane() const { return lane16() >> 4; }
    __device__ __forceinline__ uint32_t park() const { return sb + OFF_PARK + warp * 2560 + lane16(); }
    __device__ __forceinline__ const char* box(int src) const { return mb + launder(src - r) * RBOX; }
};
__device__ __forceinline__ void sched_fence(Ctx& c) {
    asm volatile("{.reg .pred p; setp.eq.s32 p, %0, 0x400000%=;\nFENCE_%=: @p nanosleep.u32 1; @p bra.uni FENCE_%=;}" :: "r"(c.eall) : "memory");
}
__device__ __forceinline__ void wait_full(Ctx& c, int k) { mbar_wait(c.sb + BAR_FULL + (k % NSLOT) * 8, (k / NSLOT) & 1, c.budget); }
__device__ __forceinline__ void release(const Ctx& c, int k) {
    if (c.rel_addr != 0 && (k < NITEMS_L - NSLOT || c.layer == 0)) mbar_arrive_cluster(c.rel_addr + (k % NSLOT) * 8);
}
template <int K> __device__ __forceinline__ void order_wait(Ctx& c) {
    if (((ORDER >> K) & 1) && c.warp >= 4) mbar_wait(c.sb + BAR_ORD + K * 8, c.layer, c.budget);
}
template <int K> __device__ __forceinline__ void order_post(const Ctx& c) {
    if (((ORDER >> K) & 1) && c.warp == 0 && c.rel_addr != 0) mbar_arrive(c.sb + BAR_ORD + K * 8);
}
template <int NV> __device__ __forceinline__ void ld_vecs(uint32_t (&v)[NV][4], const char* p, int v0) {
#pragma unroll
    for (int u = 0; u < NV; u++) ldv(v[u], p + voff(v0 + u));
}
template <int NV> __device__ __forceinline__ void publish(const Ctx& c, uint32_t (&v)[NV][4], int v0, uint32_t tag) {
#pragma unroll
    for (int u = 0; u < NV; u++) {
        v[u][0] = launder(tagged(v[u][0], tag));
        stv(c.mb + voff(v0 + u), v[u][0], v[u][1], v[u][2], v[u][3]);
    }
}
template <int NV, class F> __device__ __forceinline__ void check_vecs(Ctx& c, uint32_t (&v)[NV][4], uint32_t tag, F reload) {
    while (bad_vecs(v, tag) && --c.budget >= 0) reload();
}

__device__ __forceinline__ void probe(Ctx& c, int src, int vec) {
    const char* pp = c.mb + ((src - c.r) * RBOX - (int)c.lane16() + voff(vec) + 496);
    uint32_t v;
    do {
        asm volatile("ld.relaxed.gpu.global.u32 %0, [%1];" : "=r"(v) : "l"(pp) : "memory");
    } while (__any_sync(0xffffffffu, !(v & 1u)) && --c.budget >= 0);
}

__device__ __forceinline__ void park_x(const Ctx& c, const uint32_t (&v)[5][4]) {
    const uint32_t a = c.park();
#pragma unroll
    for (int u = 0; u < 5; u++) stsm4(a + u * 512, v[u][0], v[u][1], v[u][2], v[u][3]);
}
__device__ __forceinline__ void unpark_x(const Ctx& c, uint32_t (&v)[5][4]) {
    const uint32_t a = c.park();
#pragma unroll
    for (int u = 0; u < 5; u++) ldsm4(v[u], a + u * 512);
}
__device__ __forceinline__ void unstage(Ctx& c, uint32_t (&v)[5][4], int odd, int which) {
    const int lane = c.lane();
    const uint32_t a = c.sb + STAGE_OFF + which * 20480 + (c.warp * 16 + (lane & 15)) * 160 + (lane >> 4) * 16;
    mbar_wait(c.sb + BAR_X + which * 8, 0, c.budget);
#pragma unroll
    for (int u = 0; u < 5; u++) ldsm4(v[u], u < 4 ? a + odd * 32 + u * 32 : a + 128 - odd * 128);
}
__device__ __forceinline__ void pack_x(uint32_t (&X)[5][4], const float (&v)[40]) {
#pragma unroll
    for (int u = 0; u < 5; u++)
#pragma unroll
        for (int i = 0; i < 4; i++) X[u][i] = pack2(v[8 * u + 2 * i], v[8 * u + 2 * i + 1]);
}
__device__ __forceinline__ void unpack_x(float (&v)[40], const uint32_t (&X)[5][4]) {
#pragma unroll
    for (int u = 0; u < 5; u++)
#pragma unroll
        for (int i = 0; i < 4; i++) { v[8 * u + 2 * i] = bf_lo(X[u][i]); v[8 * u + 2 * i + 1] = bf_hi(X[u][i]); }
}
__device__ __forceinline__ void store_out(const Ctx& c, const uint32_t (&X)[5][4], const CUtensorMap* tm, int blk) {
    const int lane = c.lane(), odd = c.r & 1;
    const uint32_t tile = c.sb + OFF_PARK + c.warp * 2560;
    const uint32_t a = tile + (lane & 15) * 160 + (lane >> 4) * 16;
#pragma unroll
    for (int u = 0; u < 5; u++) stsm4(u < 4 ? a + odd * 32 + u * 32 : a + 128 - odd * 128, X[u][0], X[u][1], X[u][2], X[u][3]);
    asm volatile("fence.proxy.async.shared::cta;" ::: "memory");
    __syncwarp();
    if (elect_one()) {
        asm volatile("cp.async.bulk.tensor.2d.global.shared::cta.bulk_group [%0, {%2, %3}], [%1];"
                     :: "l"(tm), "r"(tile), "r"(640 * (c.warp >> 2) + 80 * c.r), "r"(64 * blk + 16 * (c.warp & 3)) : "memory");
        asm volatile("cp.async.bulk.commit_group;" ::: "memory");
        asm volatile("cp.async.bulk.wait_group 0;" ::: "memory");
    }
    __syncwarp();
}

template <int NB, int V0, uint32_t TAG> struct Gather {
    uint32_t buf[NB][5][4];
    __device__ __forceinline__ uint32_t (&at(int t))[5][4] { return buf[(t - 1) % NB]; }
    __device__ __forceinline__ void fetch(Ctx& c, int t) { ld_vecs(at(t), c.box(slice_at(t, c.r)), V0); }
    __device__ __forceinline__ void check(Ctx& c, int t) { check_vecs(c, at(t), TAG, [&]() { fetch(c, t); }); }
};

struct GQKV {
    float m[96], r[24];
    template <bool INIT> __device__ __forceinline__ void step(const uint32_t (&a)[5][4], uint32_t sb16, int off, int odd) {
#pragma unroll
        for (int u = 0; u < 5; u++) {
            const uint64_t dm = mkdesc(sb16 + kstep(odd, u) * 128, off, 10240, 1024, 1), dr = mkdesc(sb16 + kstep(odd, u) * 32, off + 30720, 2560, 256, 3);
            if (INIT && u == 0) { wgmma_n192_init(m, a[u], dm); wgmma_n48_init(r, a[u], dr); }
            else { wgmma_n192_acc(m, a[u], dm); wgmma_n48_acc(r, a[u], dr); }
        }
    }
};
struct GW1 {
    float m[112];
    template <bool INIT> __device__ __forceinline__ void step(const uint32_t (&a)[5][4], uint32_t sb16, int off, int odd) {
#pragma unroll
        for (int u = 0; u < 5; u++) {
            const uint64_t d = mkdesc(sb16 + kstep(odd, u) * 64, off, 5120, 512, 2);
            if (INIT && u == 0) wgmma_n224_init(m, a[u], d); else wgmma_n224_acc(m, a[u], d);
        }
    }
};

template <int K0, int LAST, uint32_t TAG, class G, class A, class Hook>
__device__ __forceinline__ void ln_head(G& g, A& a, Ctx& c, const uint32_t (&own)[5][4], const float (&xv)[40],
                                        float& rsA, float& rsB, uint32_t (&ax)[4], Hook hook, int tl0) {
    sched_fence(c);
    wg_fence();
    g.template step<true>(own, c.sb16, slot_off(K0), c.r & 1);
    wg_commit();
    if (tl0) TL(tl0 + 1);
    sched_fence(c);
    float s[4] = {0.f, 0.f, 0.f, 0.f};
#pragma unroll
    for (int j = 0; j < 10; j++) {
        s[0] += xv[4 * j] + xv[4 * j + 1];
        s[1] = fmaf(xv[4 * j], xv[4 * j], fmaf(xv[4 * j + 1], xv[4 * j + 1], s[1]));
        s[2] += xv[4 * j + 2] + xv[4 * j + 3];
        s[3] = fmaf(xv[4 * j + 2], xv[4 * j + 2], fmaf(xv[4 * j + 3], xv[4 * j + 3], s[3]));
    }
    reg_fence(s);
    wait_full(c, K0 + 1);
    hook(-1);
    a.check(c, 1);
    a.fetch(c, 2);
    uint32_t sv[2][4];
    auto sfetch = [&]() {
        const int lane = c.lane();
        const char* p = c.mb + (((lane & 3) - c.r) * RBOX + (lane >> 2) * 16 - lane * 16);
        ldv(sv[0], p + voff(V_ST)); ldv(sv[1], p + voff(V_ST) + 4 * RBOX);
    };
#pragma unroll
    for (int t = 1; t <= LAST; t++) {
        sched_fence(c);
        if (tl0) TL(tl0 + 2 + t);
        wg_fence();
        g.template step<false>(a.at(t), c.sb16, slot_off(K0 + t), t == 1 ? (c.r & 1) ^ 1 : t & 1);
        wg_commit();
        wg_wait<1>();
        release(c, K0 + t - 1);
        wait_full(c, K0 + t + 1);
        if (t == 1) {
#pragma unroll
            for (int i = 0; i < 4; i++) {
                s[i] += __shfl_xor_sync(0xffffffffu, s[i], 1);
                s[i] += __shfl_xor_sync(0xffffffffu, s[i], 2);
            }
            const int lane = c.lane();
            if ((lane & 3) == 0)
                stv(c.mb + voff(V_ST) - lane * 12, tagged(__float_as_uint(s[0]), TAG), __float_as_uint(s[1]), __float_as_uint(s[2]), __float_as_uint(s[3]));
            sched_fence(c);
        }
        a.check(c, t + 1);
        if (t == LAST) check_vecs(c, sv, TAG, sfetch);
        a.fetch(c, t + 2);
        if (t == LAST - 1) sfetch();
        hook(t);
    }
#pragma unroll
    for (int i = 0; i < 4; i++) {
        s[i] = __uint_as_float(sv[0][i]) + __uint_as_float(sv[1][i]);
        s[i] += __shfl_xor_sync(0xffffffffu, s[i], 1);
        s[i] += __shfl_xor_sync(0xffffffffu, s[i], 2);
    }
    const float mA = s[0] * (1.f / DM), mB = s[2] * (1.f / DM);
    rsA = rsq(fmaxf(fmaf(-mA, mA, s[1] * (1.f / DM)), 0.f) + LN_EPS);
    rsB = rsq(fmaxf(fmaf(-mB, mB, s[3] * (1.f / DM)), 0.f) + LN_EPS);
    const uint32_t h = pack2(mA, mB);
    const uint32_t l = pack2(mA - bf_lo(h), mB - bf_hi(h));
    const bool on = (c.lane16() & 32) == 0;
    ax[0] = on ? __byte_perm(h, l, 0x5410) : 0u;
    ax[1] = on ? __byte_perm(h, l, 0x7632) : 0u;
    ax[2] = 0u; ax[3] = 0u;
    asm volatile("" : "+r"(ax[0]), "+r"(ax[1]), "+r"(ax[2]), "+r"(ax[3]), "+f"(rsA), "+f"(rsB));
    sched_fence(c);
}

__global__ void __launch_bounds__(384, 1)
fused_layers_kernel(const __grid_constant__ Params prm, const __grid_constant__ CUtensorMap tmQM, const __grid_constant__ CUtensorMap tmQR,
                    const __grid_constant__ CUtensorMap tmWO, const __grid_constant__ CUtensorMap tmW1a, const __grid_constant__ CUtensorMap tmW1b,
                    const __grid_constant__ CUtensorMap tmW2, const __grid_constant__ CUtensorMap tmW2a, const __grid_constant__ CUtensorMap tmOut, const __grid_constant__ CUtensorMap tmX) {
    extern __shared__ __align__(1024) uint8_t smem_raw[];
    const uint32_t sb = smem_u32(smem_raw);
    const int warp = __shfl_sync(0xffffffffu, threadIdx.x >> 5, 0);
    const int lane = threadIdx.x & 31;
    asm volatile("griddepcontrol.launch_dependents;");
    const int cs = 1 << prm.lcs;
    const int cl = prm.role[blockIdx.x >> prm.lcs], p = blockIdx.x & (cs - 1);
    const int r = cl & 7, blk = (cl >> 3) + p;
    const uint16_t mask = (1 << cs) - 1;
    const int role = blk * 8 + r;
    TL(0); TLINIT

    if (warp >= 8 && elect_one()) {
        if (warp == 8) { prefetch_map(&tmQM); prefetch_map(&tmQR); prefetch_map(&tmX); }
        if (warp == 9) {
#pragma unroll
            for (int i = 0; i < NSLOT; i++) { mbar_init(sb + BAR_FULL + i * 8, 1); mbar_init(sb + BAR_EMPTY + i * 8, 8 * cs); }
            mbar_init(sb + BAR_STAGE, 8 * cs);
            mbar_init(sb + BAR_X, 1); mbar_init(sb + BAR_X + 8, 1);
            mbar_init(sb + BAR_CS, 3); mbar_init(sb + BAR_CS + 8, 3);
#pragma unroll
            for (int i = 0; i < NORD; i++) mbar_init(sb + BAR_ORD + i * 8, cs);
            asm volatile("fence.mbarrier_init.release.cluster;" ::: "memory");
        }
    }
    __syncwarp();
    asm volatile("barrier.cluster.arrive.relaxed.aligned;" ::: "memory");
    uint32_t etag0;
    asm volatile("{.reg .pred p; setp.ne.s32 p, %2, 8; mov.b32 %0, 0; @p ld.relaxed.gpu.global.u32 %0, [%1];}"
                 : "=r"(etag0) : "l"(prm.scr + (uint32_t)(G_EPOCH + role * 128 + lane * 4)), "r"(warp) : "memory");
    auto load_x = [&](int i) {
        mbar_expect(sb + BAR_X + i * 8, 20480);
        tma2d(sb + STAGE_OFF + i * 20480, &tmX, 80 * (r ^ i), 64 * blk, sb + BAR_X + i * 8);
        tma2d(sb + STAGE_OFF + i * 20480 + 10240, &tmX, 640 + 80 * (r ^ i), 64 * blk, sb + BAR_X + i * 8);
    };
    TL(10);
    asm volatile("barrier.cluster.wait.aligned;" ::: "memory");
    if (warp == 8) {
        TL(1);
        if (elect_one()) {
#pragma unroll 1
            for (int i = 0; i < 2; i++) {
                const uint32_t base = sb + i * slot_off(1), bar = sb + BAR_FULL + i * 8;
                const int row = 80 * (r ^ i);
                mbar_expect(bar, 38400);
#pragma unroll 1
                for (int n = p; n < 4; n += cs) {
                    if (n < 3) tma2d_mc(base + n * 10240, &tmQM, main_col(r) + 640 * n, row, bar, mask);
                    else tma3d_mc(base + 30720, &tmQR, rem_col(r), row, 0, bar, mask);
                }
                if (i == 0) { load_x(0); load_x(1); }
            }
        }
        __syncwarp();
        TL(2);
    }

    if (warp >= 8) {
        int budget = SPIN_BUDGET;
        asm volatile("setmaxnreg.dec.sync.aligned.u32 %0;" :: "n"(REG_HELP));
        if (warp == 8) {
            TL(5);
            if (elect_one()) {
                int slot = 2, use = 0;
#pragma unroll 1
                for (int i = 2; i < NITEMS; i++) {
                    const int k = i >= NITEMS_L ? i - NITEMS_L : i;
                    const uint32_t base = sb + slot_off(slot), bar = sb + BAR_FULL + slot * 8;
                    if (use > 0) mbar_wait(sb + BAR_EMPTY + slot * 8, (use - 1) & 1, budget);
                    if (i == 3) mbar_wait(sb + BAR_STAGE, 0, budget);
                    if (i < NSLOT) mbar_wait(sb + BAR_FULL + (i - 2) * 8, 0, budget);
                    const int n0 = (p + i) & (cs - 1);
                    if (k < 8) {
                        const int np = k < 5 ? 3 : 2, row = 80 * slice_at(k, r), col = main_col(r) + 640 * (3 - np);
                        mbar_expect(bar, np * 10240 + 7680);
#pragma unroll 1
                        for (int n = n0; n <= np; n += cs) {
                            if (n < np) tma2d_mc(base + n * 10240, &tmQM, col + 640 * n, row, bar, mask);
                            else tma3d_mc(base + n * 10240, &tmQR, rem_col(r), row, 0, bar, mask);
                        }
                    } else if (k == 8) {
                        mbar_expect(bar, 30720);
#pragma unroll 1
                        for (int n = n0; n < 3; n += cs) tma2d_mc(base + n * 10240, &tmQM, main_col(r), 80 * slice_at(5 + n, r), bar, mask);
                    } else if (k < IT_W1) {
                        mbar_expect(bar, 30720);
#pragma unroll 1
                        for (int n = n0; n < 6; n += cs) {
                            const int sl = n >= 3, a = n - 3 * sl;
                            tma2d_mc(base + n * 5120, &tmWO, a < 2 ? main_col(r) + 32 * a : rem_col(r), 80 * slice_at(2 * (k - IT_WO) + sl, r), bar, mask);
                        }
                    } else if (k < IT_W2) {
                        const bool full = k < IT_W1 + 6, pb = full ? n0 == 0 : k == IT_W1 + 7;
                        mbar_expect(bar, full ? 35840 : pb ? 40960 : 30720);
                        const int row = 80 * slice_at(full ? k - IT_W1 : 6 + n0, r);
                        if (n0 < 2) {
                            if (pb) tma3d_mc(base + n0 * 20480, &tmW1b, 0, row, 7 * r, bar, mask);
                            else tma3d_mc(base + n0 * (full ? 20480 : 15360), &tmW1a, 0, row, 7 * r + 4, bar, mask);
                        }
                    } else if (k < IT_W2 + 8) {
                        const int st = k - IT_W2, a0 = st < 6 ? 0 : 2;
                        const bool pb = hpartB(st);
                        const int atom = pb ? 8192 : 6144;
                        mbar_expect(bar, (5 - a0) * atom);
                        const int row = 224 * hsrc_at(st, r) + (pb ? 0 : 128);
#pragma unroll 1
                        for (int a = a0 + n0; a < 5; a += cs)
                            tma2d_mc(base + (a - a0) * atom, pb ? &tmW2 : &tmW2a, a < 4 ? main_col(r ^ (a >> 1)) + 32 * (a & 1) : 160 * (r >> 1) + 64, row, bar, mask);
                    } else {
                        mbar_expect(bar, 32768);
#pragma unroll 1
                        for (int n = n0; n < 4; n += cs) tma2d_mc(base + n * 8192, &tmW2, main_col(r) + 32 * (n & 1), 224 * hsrc_at(6 + (n >> 1), r), bar, mask);
                    }
                    if (i == 2) TL(3);
                    if (i == 3) { prefetch_map(&tmWO); prefetch_map(&tmW1a); prefetch_map(&tmW1b); prefetch_map(&tmW2); prefetch_map(&tmW2a); }
                    if (i == NITEMS - 1) prefetch_map(&tmOut);
                    if (++slot == NSLOT) { slot = 0; use++; }
                }
            }
            __syncwarp();
            TLDUMP(16);
        } else {
#pragma unroll 1
            for (int i = threadIdx.x - 288; i < XTRA_BYTES / 16; i += 96)
                asm volatile("st.shared.v4.u32 [%0], {%1,%1,%1,%1};" :: "r"(sb + OFF_XQM + i * 16), "r"(0) : "memory");
            asm volatile("bar.sync 5, 96;" ::: "memory");
            const uint32_t etag = (launder(etag0) & 1u) ^ 1u;
            if (lane < 10) {
                char* cs = prm.scr + (uint32_t)(G_CS + (r * 6 + warp - 9) * 5120 + blk * 320 + lane * 32);
#pragma unroll
                for (int i = 0; i < 4; i++) stv(cs + (i >> 1) * 3 * 5120 + (i & 1) * 16, etag ^ 1u, 0u, 0u, 0u);
            }
            mbar_wait(sb + BAR_X, 0, budget);
            TLH(11);
#pragma unroll 1
            for (int mat = 0; mat < 2; mat++) {
                const int lane = launder(threadIdx.x & 31), j = launder(warp) - 9;
                const int rp = lane < 30 ? (lane * 13) >> 7 : 2, ch = lane < 30 ? lane - 10 * rp : 0;
                const int col = mat ? 224 * r + 80 * j + 8 * ch : 640 * j + 80 * r + 8 * ch;
                const bool valid = !mat || (10 * j + ch < 28 && col < DFF);
                float a[8] = {0.f, 0.f, 0.f, 0.f, 0.f, 0.f, 0.f, 0.f};
                auto sum_rows = [&](const __nv_bfloat16* w0, auto pitch_c) {
                    constexpr int PITCH = decltype(pitch_c)::value;
                    const char* src = reinterpret_cast<const char*>(w0 + (40 * blk + rp) * PITCH + (valid ? col : 0));
#pragma unroll 1
                    for (int h = 0; h < 2; h++) {
                        uint32_t w[7][4];
                        const bool last = h == 0 || rp == 0;
#pragma unroll
                        for (int i = 0; i < 6; i++) ldv(w[i], src + i * 6 * PITCH);
                        ldv(w[6], src + (last ? 36 * PITCH : 0));
#pragma unroll
                        for (int i = 0; i < 7; i++)
#pragma unroll
                            for (int e = 0; e < 4; e++) {
                                const uint32_t v = (i < 6 || last) ? w[i][e] : 0u;
                                a[2 * e] += bf_lo(v); a[2 * e + 1] += bf_hi(v);
                            }
                        src += 42 * PITCH;
                    }
                };
                auto prefetch_w1 = [&]() {
                    const int c1 = 224 * r + 80 * j + 8 * ch;
                    if (10 * j + ch < 28 && c1 < DFF && !(ch & 1)) {
                        const __nv_bfloat16* pf = prm.w1 + (40 * blk + rp) * DFF + c1;
#pragma unroll
                        for (int i = 0; i < 13; i++) asm volatile("prefetch.global.L2 [%0];" :: "l"(pf + 3 * i * DFF));
                        if (rp == 0) asm volatile("prefetch.global.L2 [%0];" :: "l"(pf + 39 * DFF));
                    }
                    __syncwarp();
                };
                if (mat == 0) {
                    sum_rows(prm.wqkv, IntC<DQKV>());
                } else {
                    sum_rows(prm.w1, IntC<DFF>());
                }
                char* cs = prm.scr + (uint32_t)(G_CS + ((r * 2 + mat) * 3 + j) * 5120);
#pragma unroll
                for (int i = 0; i < 8; i++) {
                    a[i] += __shfl_down_sync(0xffffffffu, a[i], 10) + __shfl_down_sync(0xffffffffu, a[i], 20);
                    a[i] = valid ? a[i] : 0.f;
                }
                if (lane < 10) {
                    char* dst = cs + blk * 320 + lane * 32;
                    stv(dst, tagged(__float_as_uint(a[0]), etag), __float_as_uint(a[1]), __float_as_uint(a[2]), __float_as_uint(a[3]));
                    stv(dst + 16, tagged(__float_as_uint(a[4]), etag), __float_as_uint(a[5]), __float_as_uint(a[6]), __float_as_uint(a[7]));
                }
                if (mat == 0) {
                    TLH(12);
                    prefetch_w1();
                }
                cs += (lane < 20 ? lane : 0) * 16;
                a[0] = 0.f; a[1] = 0.f; a[2] = 0.f; a[3] = 0.f;
#pragma unroll 1
                for (int b0 = 0; b0 < 2;) {
                    uint32_t v[8][4];
#pragma unroll
                    for (int i = 0; i < 8; i++) ldv(v[i], cs + i * 320);
                    if (bad_vecs(v, etag) && --budget >= 0) continue;
#pragma unroll
                    for (int i = 0; i < 8; i++)
#pragma unroll
                        for (int e = 0; e < 4; e++) a[e] -= __uint_as_float(v[i][e]);
                    b0++;
                    cs += 8 * 320;
                }
                if (mat == 0) TLH(14);
                const uint32_t h0 = pack2(a[0], a[1]), h1 = pack2(a[2], a[3]);
                const uint32_t l0 = pack2(a[0] - bf_lo(h0), a[1] - bf_hi(h0)), l1 = pack2(a[2] - bf_lo(h1), a[3] - bf_hi(h1));
                const int cc = 4 * launder(lane), cm = cc - 16 * (r & 1), cw = 80 * j + cc;
                const bool mainp = cm >= 0 && cm < 64;
                const uint32_t sh = mat ? 6 : mainp ? 7 : 5;
                const uint32_t ad = sb + (mat ? OFF_XW1 + (cw >> 5) * 512 + (cw & 31) * 2 : mainp ? OFF_XQM + j * 1024 + cm * 2 : OFF_XQR + j * 256 + (cc & 15) * 2);
                if (cc < 80 && (!mat || cw < 224)) {
#pragma unroll
                    for (int row = 0; row < 4; row++) {
                        const uint32_t o = row << sh;
                        asm volatile("st.shared.v2.u32 [%0], {%1,%2};" :: "r"((ad + o) ^ ((o >> 7) << 4)), "r"(row < 2 ? h0 : l0), "r"(row < 2 ? h1 : l1) : "memory");
                    }
                }
                asm volatile("fence.proxy.async.shared::cta;" ::: "memory");
                __syncwarp();
                if (lane == 0) mbar_arrive(sb + BAR_CS + mat * 8);
                TLH(6 + mat);
            }
        }
    } else {
        TL(11);
        TL(12);
        __syncwarp();
        asm volatile("setmaxnreg.inc.sync.aligned.u32 %0;" :: "n"(REG_CONS));
        TL(14);
        Ctx c;
        c.sb = sb; c.sb16 = (sb & 0x3FFFF) >> 4; c.r = r; c.warp = warp; c.layer = 0; c.budget = SPIN_BUDGET; c.eall = __ballot_sync(0xffffffffu, !(launder(etag0) & 1u));
        c.mb = reinterpret_cast<char*>(__shfl_sync(0xffffffffu, reinterpret_cast<size_t>(prm.scr + (uint32_t)(blk * BBOX + r * RBOX + warp * WBOX + lane * 16)), lane));
        asm volatile("mapa.shared::cluster.u32 %0, %1, %2;" : "=r"(c.rel_addr) : "r"(sb + BAR_EMPTY), "r"(lane & (cs - 1)));
        c.rel_addr = __shfl_sync(0xffffffffu, lane < cs ? c.rel_addr : 0, lane);
        uint32_t X[5][4];
        float xv[40];
        unstage(c, X, r & 1, 0);
        TL(15);
        wait_full(c, 0);
        TL(13);
        unpack_x(xv, X);
        park_x(c, X);
        TL(1);

        const int r_ = r, blk_ = blk, warp_ = warp;
#define PHASE_IDS const int r = launder(r_), blk = launder(blk_), warp = launder(warp_), wg = warp >> 2, w = warp & 3; \
                  c.r = r; c.warp = warp; c.sb = launder(sb); c.sb16 = (c.sb & 0x3FFFF) >> 4; const uint32_t etag = launder(c.eall) & 1u; (void)etag; (void)blk; (void)wg; (void)w;
#pragma unroll 1
        for (int layer = 0;; layer++) {
            c.layer = layer;
            float rsA, rsB;
            uint32_t O[5][4];
            {
                PHASE_IDS
                GQKV q;
                Gather<3, V_X, 1u> ga;
                uint32_t ax[4];
                auto hook = [&](int st) {
                    if (st == -1) {
                        if (layer == 0) {
                            unstage(c, ga.buf[0], (r & 1) ^ 1, 1);
#pragma unroll
                            for (int u = 0; u < 5; u++) ga.buf[0][u][0] |= 1u;
                            if (c.rel_addr != 0) mbar_arrive_cluster(c.rel_addr + (BAR_STAGE - BAR_EMPTY));
                        } else {
                            ga.fetch(c, 1);
                        }
                    }
                    if (st >= 1 && layer == 0) {
                        if (st == CLR_HALO && w == 3) {
#pragma unroll
                            for (int u = 0; u < 6; u++) stv(c.mb + voff(V_HALO + u), etag ^ 1u, 0u, 0u, 0u);
                        }
#pragma unroll
                        for (int u = 0; u < 5; u++)
                            if (st == ((CLR_O >> (4 * u)) & 15)) stv(c.mb + voff(V_O + u), 0u, 0u, 0u, 0u);
                    }
                };
                publish(c, X, V_X, 1u);
                ln_head<0, 4, 1u>(q, ga, c, X, xv, rsA, rsB, ax, hook, (TLSEL == 1 + layer * 4) ? 50 : 0);
                float qm[32], kv[64];
                wg_wait<0>();
                reg_fence(q.m);
                rename<32, 0>(qm, q.m);
                rename<64, 32>(kv, q.m);
#pragma unroll
                for (int st = 5; st < 8; st++) {
                    if (st == 7) order_wait<0>(c);
                    wg_fence();
#pragma unroll
                    for (int u = 0; u < 5; u++) {
                        wgmma_n128_acc(kv, ga.at(st)[u], mkdesc(c.sb16, slot_off(st) + kstep(st & 1, u) * 2048, 10240, 1024, 1));
                        wgmma_n48_acc(q.r, ga.at(st)[u], mkdesc(c.sb16, slot_off(st) + 20480 + kstep(st & 1, u) * 512, 2560, 256, 3));
                    }
                    if (st == 7) {
                        wgmma_n128_acc(kv, ax, mkdesc(c.sb16, OFF_XQM + 1024, 1024, 0, 1));
                        wgmma_n48_acc(q.r, ax, mkdesc(c.sb16, OFF_XQR, 256, 0, 3));
                    }
                    wg_commit();
                    if (st == 7) order_post<0>(c);
                    if (st > 5) wg_wait<1>();
                    release(c, st - 1);
                    wait_full(c, st + 1);
                    if (st == 5) {
                        ga.check(c, 6);
                        ga.fetch(c, 7);
                        sched_fence(c);
                    }
                    if (st == 6) {
                        if (layer == 0) mbar_wait(c.sb + BAR_CS, 0, c.budget);
                        ga.check(c, 7);
                    }
                }
                float rk1[2], rk2[2];
                {
                    const int t8 = (c.lane16() >> 1) & 24;
#pragma unroll
                    for (int e = 0; e < 2; e++) {
                        rk2[e] = __shfl_sync(0xffffffffu, rsB, t8 + 4 * e);
                        rk1[e] = __shfl_sync(0xffffffffu, rsA, t8 + 4 * e);
                    }
                }
                auto q_steps = [&](int n0, int n1) {
                    wg_fence();
#pragma unroll
                    for (int n = n0; n < n1; n++) {
                        if (n < 15) wgmma_n64_acc(qm, ga.at(5 + n / 5)[n % 5], mkdesc(c.sb16, slot_off(8) + (n / 5 * 5 + kstep((5 + n / 5) & 1, n % 5)) * 2048, 1024, 1024, 1));
                        else wgmma_n64_acc(qm, ax, mkdesc(c.sb16, OFF_XQM, 1024, 0, 1));
                    }
                    wg_commit();
                };
                q_steps(0, 7);
                wg_wait<1>();
                reg_fence(kv);
                reg_fence(q.r);
                release(c, 7);
                TL(2 + layer * 16);
                uint32_t T[3][10][2];
                auto pack_tiles = [&](int pc, int h, bool odd) {
#pragma unroll
                    for (int j = 0; j < 10; j++) {
                        const bool isrem = odd ? j < 2 : j >= 8;
                        const int e = isrem ? pc * 8 + 4 * (j & 1) + 2 * h : 4 * ((odd ? j + 6 : j) & 7) + 2 * h;
                        if (isrem) T[pc][j][h] = pack2(q.r[e], q.r[e + 1]);
                        else T[pc][j][h] = pc == 0 ? pack2(qm[e], qm[e + 1]) : pack2(kv[(pc - 1) * 32 + e], kv[(pc - 1) * 32 + e + 1]);
                    }
                };
                if (r & 1) { pack_tiles(1, 1, true); pack_tiles(2, 1, true); }
                else { pack_tiles(1, 1, false); pack_tiles(2, 1, false); }
                auto hreg = [&](int n) -> uint32_t& { return n < 8 ? T[1][n + (n + 2) / 4][1] : n < 10 ? T[1][5 * n - 38][1] : T[2][n - 10][1]; };
                if (w == 3) {
                    char* hg = c.mb + layer * (2 * PLANE);
#pragma unroll
                    for (int u = 0; u < 5; u++) {
                        hreg(4 * u) = tagged(hreg(4 * u), etag);
                        stv(hg + voff(V_HALO + u), hreg(4 * u), hreg(4 * u + 1), hreg(4 * u + 2), hreg(4 * u + 3));
                    }
                    stv(hg + voff(V_HALO + 5), tagged(__float_as_uint(rk2[0]), etag), __float_as_uint(rk2[1]), 0u, 0u);
                }
                if (r & 1) { pack_tiles(1, 0, true); pack_tiles(2, 0, true); }
                else { pack_tiles(1, 0, false); pack_tiles(2, 0, false); }
                unpark_x(c, X);
                q_steps(7, 16);
                if (w < 3) {
                    const uint32_t hs = c.park();
#pragma unroll
                    for (int u = 0; u < 5; u++) stsm4(hs + u * 512, hreg(4 * u), hreg(4 * u + 1), hreg(4 * u + 2), hreg(4 * u + 3));
                    if (c.lane16() < 64) asm volatile("st.shared.v2.f32 [%0], {%1,%2};" :: "r"(c.sb + OFF_RK + warp * 32 + (c.lane16() >> 1)), "f"(rk2[0]), "f"(rk2[1]) : "memory");
                }
                asm volatile("bar.sync %0, 128;" :: "r"(1 + wg) : "memory");
                uint32_t H[6][4];
                auto hfetch = [&]() { ld_vecs(H, c.mb + (3 * WBOX - BBOX) + layer * (2 * PLANE), V_HALO); };
                if (w > 0) {
                    const uint32_t hs = c.park() - 2560;
                    ldsm4(H[0], hs); ldsm4(H[1], hs + 512);
                    asm volatile("ldmatrix.sync.aligned.m8n8.x2.shared.b16 {%0,%1}, [%2];" : "=r"(H[2][0]), "=r"(H[2][1]) : "r"(hs + 1024) : "memory");
                    asm volatile("ldmatrix.sync.aligned.m8n8.x2.trans.shared.b16 {%0,%1}, [%2];" : "=r"(H[2][2]), "=r"(H[2][3]) : "r"(hs + 1280) : "memory");
                    ldsm4t(H[3], hs + 1536); ldsm4t(H[4], hs + 2048);
                    asm volatile("ld.shared.v2.u32 {%0,%1}, [%2];" : "=r"(H[5][0]), "=r"(H[5][1]) : "r"(c.sb + OFF_RK + warp * 32 - 32 + ((c.lane16() >> 1) & 24)) : "memory");
                    H[5][2] = 0u; H[5][3] = 0u;
                } else if (blk > 0) {
                    hfetch();
                } else {
#pragma unroll
                    for (int u = 0; u < 6; u++) { H[u][0] = 0u; H[u][1] = 0u; H[u][2] = 0u; H[u][3] = 0u; }
                }
                auto hK = [&](int j) { return j == 2 ? H[2][0] : j == 7 ? H[2][1] : H[(j - (j + 2) / 5) >> 2][(j - (j + 2) / 5) & 3]; };
                auto hV = [&](int j) { return H[(j + 10) >> 2][(j + 10) & 3]; };
                uint32_t Vt1[10], Vt2[10];
#pragma unroll
                for (int j = 0; j < 10; j++) { Vt1[j] = movm(T[2][j][0]); Vt2[j] = movm(T[2][j][1]); }
                wg_wait<0>();
                reg_fence(qm);
                release(c, 8);
                if (r & 1) { pack_tiles(0, 0, true); pack_tiles(0, 1, true); }
                else { pack_tiles(0, 0, false); pack_tiles(0, 1, false); }
                TL(3 + layer * 16);
                const int g = c.lane() >> 2, t = c.lane() & 3;
                const bool sel0 = 2 * t > g, sel1 = 2 * t + 1 > g;
                const float cs = 0.22360679774997896f * 1.4426950408889634f;
                const float kB0 = sel0 ? rk1[0] : rk2[0], kB1 = sel1 ? rk1[1] : rk2[1];
                const float fB0 = rsB * cs * kB0, fB1 = rsB * cs * kB1;
                float lA0[4], lA1[4], lB0[4], lB1[4];
                uint32_t qs[4][2];
#pragma unroll
                for (int h = 0; h < 4; h++) {
                    const int f0 = 5 * (h >> 1) + 3 * (h & 1), f1 = f0 + 1, s = 5 * (h >> 1) + 2;
                    const bool keep = (h & 1) ? (t >= 2) : (t < 2);
                    qs[h][0] = keep ? T[0][s][0] : 0u; qs[h][1] = keep ? T[0][s][1] : 0u;
                    float s1[4], s2[4];
                    mma_k8_init(s1, qs[h][0], qs[h][1], T[1][s][0]);
                    mma_k8_init(s2, qs[h][0], qs[h][1], T[1][s][1]);
                    mma_k16_acc(s1, T[0][f0][0], T[0][f0][1], T[0][f1][0], T[0][f1][1], T[1][f0][0], T[1][f1][0]);
                    mma_k16_acc(s2, T[0][f0][0], T[0][f0][1], T[0][f1][0], T[0][f1][1], T[1][f0][1], T[1][f1][1]);
                    lA0[h] = s1[0]; lA1[h] = s1[1];
                    lB0[h] = (sel0 ? s1[2] : s2[2]) * fB0;
                    lB1[h] = (sel1 ? s1[3] : s2[3]) * fB1;
                }
                wait_full(c, IT_WO);
                if (w == 0 && blk > 0) {
                    check_vecs(c, H, etag, hfetch);
#pragma unroll
                    for (int n = 10; n < 20; n++) H[n >> 2][n & 3] = movm(H[n >> 2][n & 3]);
                }
                const bool first = (blk == 0) && (w == 0);
                const float kA0 = sel0 ? __uint_as_float(H[5][0]) : rk1[0], kA1 = sel1 ? __uint_as_float(H[5][1]) : rk1[1];
                const float fA0 = rsA * cs * kA0, fA1 = rsA * cs * kA1;
                const float bA0 = (first && sel0) ? -INFINITY : 0.f, bA1 = (first && sel1) ? -INFINITY : 0.f;
                const uint32_t M = (sel0 ? 0x0000ffffu : 0u) | (sel1 ? 0xffff0000u : 0u);
#pragma unroll
                for (int h = 0; h < 4; h++) {
                    const int f0 = 5 * (h >> 1) + 3 * (h & 1), f1 = f0 + 1, s = 5 * (h >> 1) + 2;
                    float s0[4];
                    mma_k8_init(s0, qs[h][0], qs[h][1], hK(s));
                    mma_k16_acc(s0, T[0][f0][0], T[0][f0][1], T[0][f1][0], T[0][f1][1], hK(f0), hK(f1));
                    lA0[h] = fmaf(sel0 ? s0[0] : lA0[h], fA0, bA0);
                    lA1[h] = fmaf(sel1 ? s0[1] : lA1[h], fA1, bA1);
                }
                uint32_t pA[4], pB[4];
#pragma unroll
                for (int h = 0; h < 4; h++) {
                    float mA = fmaxf(lA0[h], lA1[h]), mB = fmaxf(lB0[h], lB1[h]);
                    mA = fmaxf(mA, __shfl_xor_sync(0xffffffffu, mA, 1));
                    mB = fmaxf(mB, __shfl_xor_sync(0xffffffffu, mB, 1));
                    mA = fmaxf(mA, __shfl_xor_sync(0xffffffffu, mA, 2));
                    mB = fmaxf(mB, __shfl_xor_sync(0xffffffffu, mB, 2));
                    const float eA0 = ex2(lA0[h] - mA), eA1 = ex2(lA1[h] - mA), eB0 = ex2(lB0[h] - mB), eB1 = ex2(lB1[h] - mB);
                    float sA = eA0 + eA1, sB = eB0 + eB1;
                    sA += __shfl_xor_sync(0xffffffffu, sA, 1);
                    sB += __shfl_xor_sync(0xffffffffu, sB, 1);
                    sA += __shfl_xor_sync(0xffffffffu, sA, 2);
                    sB += __shfl_xor_sync(0xffffffffu, sB, 2);
                    const float iA = rcp(sA), iB = rcp(sB);
                    pA[h] = pack2(eA0 * kA0 * iA, eA1 * kA1 * iA);
                    pB[h] = pack2(eB0 * kB0 * iB, eB1 * kB1 * iB);
                }
#pragma unroll
                for (int h = 0; h < 4; h++) {
                    const int f0 = 5 * (h >> 1) + 3 * (h & 1), s = 5 * (h >> 1) + 2;
                    const uint32_t ap = pA[h] & M, a0 = pA[h] & ~M, a1 = pB[h] & M, a3 = pB[h] & ~M;
#pragma unroll
                    for (int i = 0; i < 3; i++) {
                        const int j = i < 2 ? f0 + i : s;
                        float o[4];
                        mma_k8_init(o, ap, 0u, hV(j));
                        mma_k16_acc(o, a0, a1, 0u, a3, Vt1[j], Vt2[j]);
                        const uint32_t o0 = pack2(o[0], o[1]), o1 = pack2(o[2], o[3]);
                        uint32_t& d0 = O[j >> 1][2 * (j & 1)];
                        uint32_t& d1 = O[j >> 1][2 * (j & 1) + 1];
                        if (i < 2 || (h & 1) == 0) { d0 = o0; d1 = o1; }
                        else { d0 = t >= 2 ? o0 : d0; d1 = t >= 2 ? o1 : d1; }
                    }
                }
                publish(c, O, V_O, 1u);
            }
            TL(4 + layer * 16);
            {
                PHASE_IDS
                Gather<7, V_O, 1u> ga;
                sched_fence(c);
                unpack_x(xv, X);
#pragma unroll
                for (int st = 0; st < 8; st++) {
                    if (st == 6) order_wait<1>(c);
                    wg_fence();
#pragma unroll
                    for (int u = 0; u < 5; u++)
                        wgmma_n80_acc(xv, st == 0 ? O[u] : ga.at(st > 0 ? st : 1)[u], mkdesc(c.sb16, slot_off(IT_WO + st / 2) + (st & 1) * 15360 + u * 1024, 5120, 512, 2));
                    wg_commit();
                    if (st == 7) order_post<1>(c);
                    if (st > 0 && (st & 1) == 0) { wg_wait<1>(); release(c, IT_WO + st / 2 - 1); }
                    const bool batch = st == 0 || st == WO_B1 || st == WO_B2;
                    if (st & 1) wait_full(c, IT_WO + st / 2 + 1); else if (batch) sched_fence(c);
                    if (st == 0) {
#pragma unroll
                        for (int i = 1; i <= WO_B1; i++) ga.fetch(c, i);
                    }
                    if (batch) {
                        const int e0 = st == 0 ? WO_B1 : st == WO_B1 ? WO_B2 : 7, e1 = st == 0 ? WO_B2 : 7;
#pragma unroll
                        for (int i = st + 1; i <= e0; i++) ga.check(c, i);
#pragma unroll
                        for (int i = e0 + 1; i <= e1; i++) ga.fetch(c, i);
                        if (e1 > e0) sched_fence(c);
                    }
                    if (TLSEL == 2 + layer * 4) TL(50 + st);
                }
                wg_wait<0>();
                reg_fence(xv);
                release(c, IT_W1 - 1);
                TL(5 + layer * 16);
                pack_x(X, xv);
                if (DBG_STAGE == 1 + 2 * layer) store_out(c, X, &tmOut, blk);
                park_x(c, X);
                publish(c, X, V_X, 0u);
            }
            TL(6 + layer * 16);
            {
                PHASE_IDS
                const uint32_t ltag = layer ^ 1u;
                uint32_t Ha[6][4], Hb[8][4];
                {
                    GW1 f;
                    Gather<3, V_X, 0u> ga;
                    uint32_t ax[4];
                    ln_head<IT_W1, 5, 0u>(f, ga, c, X, xv, rsA, rsB, ax, [&](int st) {
                        if (st == -1) ga.fetch(c, 1);
                        if (st == 2 && layer == 0) {
                            stv(c.mb + voff(V_HB + 7), 0u, 0u, 0u, 0u);
                            stv(c.mb + voff(V_HA + 5), 0u, 0u, 0u, 0u);
                        }
                        if (st == 3 && layer == 0 && w == 3) {
#pragma unroll
                            for (int u = 0; u < 6; u++) stv(c.mb + voff(V_HALO + 10 + u), etag ^ 1u, 0u, 0u, 0u);
                        }
                    }, (TLSEL == 3 + layer * 4) ? 50 : 0);
                    float fa[48], fb[64];
                    if (layer == 0) mbar_wait(c.sb + BAR_CS + 8, 0, c.budget);
                    order_wait<2>(c);
                    wg_wait<0>();
                    reg_fence(f.m);
                    rename<64, 0>(fb, f.m);
                    rename<48, 64>(fa, f.m);
#pragma unroll
                    for (int st = 6; st < 8; st++) {
                        wg_fence();
#pragma unroll
                        for (int u = 0; u < 5; u++)
                            wgmma_n96_acc(fa, ga.at(st)[u], mkdesc(c.sb16, slot_off(IT_W1 + 6) + (st - 6) * 15360 + kstep(st & 1, u) * 1024, 5120, 512, 2));
                        if (st == 6) {
                            order_post<2>(c);
                            release(c, IT_W1 + 5);
                            wait_full(c, IT_W1 + 7);
                            ga.check(c, 7);
                        }
                    }
                    wgmma_n96_acc(fa, ax, mkdesc(c.sb16, OFF_XW1 + 2048, 512, 0, 2));
                    wg_commit();
                    auto b_steps = [&](int n0, int n1) {
                        wg_fence();
#pragma unroll
                        for (int n = n0; n < n1; n++) {
                            if (n < 10) wgmma_n128_acc(fb, ga.at(6 + n / 5)[n % 5], mkdesc(c.sb16, slot_off(IT_W1 + 7) + (n / 5) * 20480 + kstep(n / 5, n % 5) * 1024, 5120, 512, 2));
                            else wgmma_n128_acc(fb, ax, mkdesc(c.sb16, OFF_XW1, 512, 0, 2));
                        }
                        wg_commit();
                    };
                    b_steps(0, 7);
                    wait_full(c, IT_W2);
                    wg_wait<1>();
                    reg_fence(fa);
                    release(c, IT_W1 + 6);
                    TL(7 + layer * 16);
#pragma unroll
                    for (int k = 0; k < 6; k++)
#pragma unroll
                        for (int i = 0; i < 4; i++) Ha[k][i] = pack2_relu(fa[8 * k + 2 * i], fa[8 * k + 2 * i + 1]);
                    publish(c, Ha, V_HA, ltag);
                    sched_fence(c);
                    b_steps(7, 11);
                    wg_wait<0>();
                    reg_fence(fb);
#pragma unroll
                    for (int k = 0; k < 8; k++)
#pragma unroll
                        for (int i = 0; i < 4; i++) Hb[k][i] = pack2_relu(fb[8 * k + 2 * i], fb[8 * k + 2 * i + 1]);
                    sched_fence(c);
                }
                float acc[80];
                uint32_t bufa[3][6][4], bufb[3][8][4];
                auto step_a = [&](int st, const uint32_t (&a)[6][4]) {
                    wg_fence();
#pragma unroll
                    for (int k = 0; k < 6; k++) {
                        const uint64_t d = mkdesc(c.sb16, slot_off(IT_W2 + st) + k * 1024, 6144, 512, 2);
                        if (st == 0 && k == 0) wgmma_n160_init(acc, a[k], d); else wgmma_n160_acc(acc, a[k], d);
                    }
                    wg_commit();
                };
                auto step_b = [&](int st, const uint32_t (&a)[8][4]) {
                    wg_fence();
#pragma unroll
                    for (int k = 0; k < 8; k++) wgmma_n160_acc(acc, a[k], mkdesc(c.sb16, slot_off(IT_W2 + st) + k * 1024, 8192, 512, 2));
                    wg_commit();
                };
                auto hprobe = [&](int vec) { if (layer == 0) probe(c, ((c.lane16() >> 3) & 6) + (r & 1), vec); };
                auto hfetch = [&](int st) {
                    if (st < 5) ld_vecs(bufa[st < 5 ? st - 2 : 0], c.box(hsrc_at(st, r)), V_HA);
                    else ld_vecs(bufb[st < 5 ? 0 : st - 5], c.box(hsrc_at(st, r)), V_HB);
                };
                auto hcheck = [&](int st) {
                    if (st < 5) check_vecs(c, bufa[st < 5 ? st - 2 : 0], ltag, [&]() { hfetch(st); });
                    else check_vecs(c, bufb[st < 5 ? 0 : st - 5], ltag, [&]() { hfetch(st); });
                };
                step_a(0, Ha);
                release(c, IT_W1 + 7);
                wait_full(c, IT_W2 + 1);
                hprobe(V_HA + 5);
                hfetch(2);
#pragma unroll
                for (int k = 0; k < 8; k++) Hb[k][0] = launder(tagged(Hb[k][0], ltag));
                auto send_b = [&](int k0, int k1) {
#pragma unroll
                    for (int k = k0; k < k1; k++) stv(c.mb + voff(V_HB + k), Hb[k][0], Hb[k][1], Hb[k][2], Hb[k][3]);
                };
                send_b(0, HB0);
                sched_fence(c);
#pragma unroll
                for (int st = 1; st < 6; st++) {
                    if (st == 1) step_b(1, Hb); else if (st < 5) step_a(st, bufa[st > 1 && st < 5 ? st - 2 : 0]); else step_b(st, bufb[0]);
                    wg_wait<1>();
                    release(c, IT_W2 + st - 1);
                    wait_full(c, IT_W2 + st + 1);
                    hcheck(st + 1);
                    if (st == 3) hprobe(V_HB + 7);
                    hfetch(st + 2);
                    if (st == 1) send_b(HB0, HB1);
                    if (st == 2) send_b(HB1, 8);
                    sched_fence(c);
                    if (layer == 1) TL(40 + st);
                }
                order_wait<3>(c);
                wg_wait<0>();
                reg_fence(acc);
                float own[32], par[48];
                rename<48, 32>(par, acc);
                rename<32, 0>(own, acc);
#pragma unroll
                for (int st = 6; st < 8; st++) {
                    if (st == 7) { order_post<3>(c); release(c, IT_W2 + 5); wait_full(c, IT_W2 + 7); hcheck(7); order_wait<4>(c); }
                    wg_fence();
#pragma unroll
                    for (int k = 0; k < 8; k++) wgmma_n96_acc(par, bufb[st - 5][k], mkdesc(c.sb16, slot_off(IT_W2 + st) + k * 1024, 8192, 512, 2));
                    wg_commit();
                }
                order_post<4>(c);
                wait_full(c, IT_W2 + 8);
                auto own_step = [&](int i) {
                    wg_fence();
#pragma unroll
                    for (int k = 0; k < 8; k++) wgmma_n64_acc(own, bufb[1 + i][k], mkdesc(c.sb16, slot_off(IT_W2 + 8) + i * 16384 + k * 1024, 8192, 512, 2));
                    wg_commit();
                };
                own_step(0);
                wg_wait<1>();
                reg_fence(par);
                release(c, IT_W2 + 6);
                release(c, IT_W2 + 7);
                float rem[8];
                uint32_t P[5][4];
                {
                    const bool odd = r & 1;
#pragma unroll
                    for (int u = 0; u < 5; u++)
#pragma unroll
                        for (int i = 0; i < 4; i++) {
                            const int e = 8 * u + 2 * i;
                            if (u < 4) P[u][i] = pack2(par[e], par[e + 1]);
                            else P[u][i] = pack2(odd ? par[e] : par[e + 8], odd ? par[e + 1] : par[e + 9]);
                        }
                    publish(c, P, V_O, 0u);
#pragma unroll
                    for (int i = 0; i < 8; i++) rem[i] = odd ? par[40 + i] : par[32 + i];
                }
                sched_fence(c);
                own_step(1);
                if (layer == 1) TL(47);
                sched_fence(c);
                auto pfetch = [&]() { ld_vecs(P, c.box(r ^ 1), V_O); };
                pfetch();
                unpark_x(c, X);
                wg_wait<0>();
                reg_fence(own);
                release(c, IT_W2 + 8);
#pragma unroll
                for (int u = 0; u < 5; u++)
#pragma unroll
                    for (int i = 0; i < 4; i++) {
                        const float rs = (i & 1) ? rsB : rsA;
                        const int e = 8 * u + 2 * i;
                        xv[e] = fmaf(rs, u < 4 ? own[e & 31] : rem[e & 7], bf_lo(X[u][i]));
                        xv[e + 1] = fmaf(rs, u < 4 ? own[(e + 1) & 31] : rem[(e + 1) & 7], bf_hi(X[u][i]));
                    }
                reg_fence(xv);
                if (layer == 0) wait_full(c, 0); else sched_fence(c);
                check_vecs(c, P, 0u, pfetch);
                TL(8 + layer * 16);
#pragma unroll
                for (int u = 0; u < 5; u++)
#pragma unroll
                    for (int i = 0; i < 4; i++) {
                        const float rs = (i & 1) ? rsB : rsA;
                        const int e = 8 * u + 2 * i;
                        xv[e] = fmaf(rs, bf_lo(P[u][i]), xv[e]);
                        xv[e + 1] = fmaf(rs, bf_hi(P[u][i]), xv[e + 1]);
                    }
                pack_x(X, xv);
                if (layer == 1) break;
                if (DBG_STAGE == 2) store_out(c, X, &tmOut, blk);
                park_x(c, X);
            }
            TL(9 + layer * 16);
        }
        if (DBG_STAGE == 4) store_out(c, X, &tmOut, blk);
        TL(25);
        TLDUMP(64);
        if (warp == 0) reinterpret_cast<unsigned*>(prm.scr + G_EPOCH + role * 128)[c.lane()] = c.eall;
    }
}

typedef CUresult (*EncodeFn)(CUtensorMap*, CUtensorMapDataType, cuuint32_t, void*, const cuuint64_t*, const cuuint64_t*,
                             const cuuint32_t*, const cuuint32_t*, CUtensorMapInterleave, CUtensorMapSwizzle,
                             CUtensorMapL2promotion, CUtensorMapFloatOOBfill);

void encode(EncodeFn fn, CUtensorMap* tm, const void* ptr, int rank, const cuuint64_t* dims, const cuuint64_t* strides,
            const cuuint32_t* box, CUtensorMapSwizzle sw) {
    const cuuint32_t es[3] = {1, 1, 1};
    fn(tm, CU_TENSOR_MAP_DATA_TYPE_BFLOAT16, rank, const_cast<void*>(ptr), dims, strides, box, es, CU_TENSOR_MAP_INTERLEAVE_NONE, sw,
       CU_TENSOR_MAP_L2_PROMOTION_NONE, CU_TENSOR_MAP_FLOAT_OOB_FILL_NONE);
}

__global__ void occupancy_probe_kernel() {}

struct Plan { int lcs, na, nb; uint8_t a[64], b[64]; };
Plan make_plan(int lcs) {
    Plan pl;
    pl.lcs = 1; pl.na = 64; pl.nb = 0;
    for (int i = 0; i < 64; i++) { pl.a[i] = ((i & 7) << 4) | (i >> 3); pl.b[i] = 0; }
    cudaFuncSetAttribute(occupancy_probe_kernel, cudaFuncAttributeMaxDynamicSharedMemorySize, SMEM_BYTES);
    cudaFuncSetAttribute(occupancy_probe_kernel, cudaFuncAttributeNonPortableClusterSizeAllowed, 1);
    int N[17] = {0};
    for (int cs = 2; cs <= 16; cs++) {
        cudaLaunchConfig_t cfg = {};
        cfg.gridDim = dim3(cs * 8); cfg.blockDim = dim3(384); cfg.dynamicSmemBytes = SMEM_BYTES;
        cudaLaunchAttribute at[1];
        at[0].id = cudaLaunchAttributeClusterDimension;
        at[0].val.clusterDim.x = cs; at[0].val.clusterDim.y = 1; at[0].val.clusterDim.z = 1;
        cfg.attrs = at; cfg.numAttrs = 1;
        if (cudaOccupancyMaxActiveClusters(&N[cs], occupancy_probe_kernel, &cfg) != cudaSuccess) { cudaGetLastError(); return pl; }
    }
    int ge[10] = {0};
    for (int k = 5; k <= 8; k++) ge[k] = N[2 * k];
    ge[9] = N[9] - ge[5];
    ge[4] = N[8] - ge[8];
    ge[3] = N[6] - ge[6] - ge[9];
    ge[2] = N[4] - ge[4] - ge[6] - ge[8];
    ge[1] = ge[2];
    int total = 0;
    for (int k = 1; k <= 9; k++) { if (ge[k] < 0 || ge[k] > 16 || (k > 1 && ge[k] > ge[k - 1])) return pl; total += ge[k]; }
    const int singles = N[2] - total;
    if (singles < 0 || N[2] < 64) return pl;
    const int cs = 1 << lcs, tp = cs / 2, want = 128 / cs, na = N[cs] < want ? N[cs] : want;
    int col[64], cnt[17] = {0}, n = 0;
    if (lcs == 1) for (; n < singles && n < na; n++) col[n] = 16;
    for (int k = tp; k <= 9; k += tp)
        for (int j = ge[k] - 1; j >= 0 && n < na; j--) col[n++] = (cnt[j]++ < 16 / cs) ? j : 16;
    if (n != na) return pl;
    pl.lcs = lcs; pl.na = na; pl.nb = (want - na) * tp;
    auto rank_of = [](int q) { return QPAR ? 2 * (q & 3) + (q >> 2) : q; };
    int pos = 0;
    for (int j = 0; j <= 16; j++)
        for (int i = 0; i < na; i++)
            if (col[i] == (j < 8 ? (int)((COLPERM >> (4 * j)) & 15) : j)) { pl.a[i] = (((pos >> 3) * cs) << 3) | rank_of(pos & 7); pos++; }
    for (int i = 0; i < pl.nb; i++) { const int q = na + i / tp; pl.b[i] = (((q >> 3) * cs + 2 * (i % tp)) << 3) | rank_of(q & 7); }
    return pl;
}

}

extern "C" void kernel_launch(void* const* d_in, const int* in_sizes, int n_in, void* d_out, int out_size) {
    const __nv_bfloat16* x = (const __nv_bfloat16*)d_in[0];
    const __nv_bfloat16* wqkv = (const __nv_bfloat16*)d_in[1];
    const __nv_bfloat16* wo = (const __nv_bfloat16*)d_in[2];
    const __nv_bfloat16* w1 = (const __nv_bfloat16*)d_in[4];
    const __nv_bfloat16* w2 = (const __nv_bfloat16*)d_in[5];

    void* fnp = nullptr;
    cudaDriverEntryPointQueryResult qr;
    cudaGetDriverEntryPoint("cuTensorMapEncodeTiled", &fnp, cudaEnableDefault, &qr);
    EncodeFn fn = (EncodeFn)fnp;
    CUtensorMap tmQM, tmQR, tmWO, tmW1a, tmW1b, tmW2, tmW2a, tmOut, tmX;
    {
        const cuuint64_t dims[3] = {640, 640, 3}, strides[2] = {DQKV * 2, 640 * 2};
        const cuuint64_t dims2[2] = {DQKV, 640};
        const cuuint32_t bm[2] = {64, 80}, br[3] = {16, 80, 3};
        encode(fn, &tmQM, wqkv, 2, dims2, strides, bm, CU_TENSOR_MAP_SWIZZLE_128B);
        encode(fn, &tmQR, wqkv, 3, dims, strides, br, CU_TENSOR_MAP_SWIZZLE_32B);
    }
    {
        const cuuint64_t dims[2] = {640, 640}, strides[1] = {640 * 2};
        const cuuint32_t box[2] = {32, 80};
        encode(fn, &tmWO, wo, 2, dims, strides, box, CU_TENSOR_MAP_SWIZZLE_64B);
    }
    {
        const cuuint64_t dims[3] = {32, 640, 54}, strides[2] = {DFF * 2, 64};
        const cuuint32_t boxa[3] = {32, 80, 3}, boxb[3] = {32, 80, 4};
        encode(fn, &tmW1a, w1, 3, dims, strides, boxa, CU_TENSOR_MAP_SWIZZLE_64B);
        encode(fn, &tmW1b, w1, 3, dims, strides, boxb, CU_TENSOR_MAP_SWIZZLE_64B);
    }
    {
        const cuuint64_t dims[2] = {640, DFF}, strides[1] = {640 * 2};
        const cuuint32_t box[2] = {32, 128}, boxa[2] = {32, 96};
        encode(fn, &tmW2, w2, 2, dims, strides, box, CU_TENSOR_MAP_SWIZZLE_64B);
        encode(fn, &tmW2a, w2, 2, dims, strides, boxa, CU_TENSOR_MAP_SWIZZLE_64B);
    }
    {
        const cuuint64_t dims[2] = {1280, 1024}, strides[1] = {1280 * 2};
        const cuuint32_t box[2] = {80, 16};
        encode(fn, &tmOut, d_out, 2, dims, strides, box, CU_TENSOR_MAP_SWIZZLE_NONE);
        const cuuint32_t boxx[2] = {80, 64};
        encode(fn, &tmX, x, 2, dims, strides, boxx, CU_TENSOR_MAP_SWIZZLE_NONE);
    }
    cudaFuncSetAttribute(fused_layers_kernel, cudaFuncAttributeMaxDynamicSharedMemorySize, SMEM_LAUNCH);
    const Plan pl = make_plan(LCS);
    Params prm;
    void* scr = nullptr;
    cudaGetSymbolAddress(&scr, g_scratch);
    prm.scr = (char*)scr;
    prm.wqkv = wqkv; prm.w1 = w1;
    for (int part = 0; part < (pl.nb ? 2 : 1); part++) {
        prm.lcs = part ? 1 : pl.lcs;
        for (int i = 0; i < 64; i++) prm.role[i] = part ? pl.b[i] : pl.a[i];
        cudaLaunchConfig_t cfg = {};
        cfg.gridDim = dim3((part ? pl.nb : pl.na) << prm.lcs); cfg.blockDim = dim3(384); cfg.dynamicSmemBytes = SMEM_LAUNCH;
        cfg.stream = cudaStreamPerThread;
        cudaLaunchAttribute at[2];
        at[0].id = cudaLaunchAttributeClusterDimension;
        at[0].val.clusterDim.x = 1 << prm.lcs; at[0].val.clusterDim.y = 1; at[0].val.clusterDim.z = 1;
        at[1].id = cudaLaunchAttributeProgrammaticStreamSerialization;
        at[1].val.programmaticStreamSerializationAllowed = 1;
        cfg.attrs = at; cfg.numAttrs = part ? 2 : 1;
        cudaLaunchKernelEx(&cfg, fused_layers_kernel, prm, tmQM, tmQR, tmWO, tmW1a, tmW1b, tmW2, tmW2a, tmOut, tmX);
    }
}
```

```cpp
#include <cuda_runtime.h>
#include <cuda_bf16.h>
#include <cuda.h>
#include <stdint.h>

#define DBG_STAGE 4
#define TLSEL 0
#define WO_F0 2
#define WO_CHK 0x77774422u
#define WO_FET 0x77777744u
#define LCS 2
#define QPAR 0
#define COLPERM 0x76543210u
#define TLL 1
#define GP 0
#define OW1 6
#define QPOS 1
#define QN0 7
#define QPOST 1
#define G6AT 1
#define ORDER 0x1f
#define TLW 0
#define CLR_HALO 1
#define CLR_O 0x44332
#define HB0 4
#define HB1 4

namespace {

constexpr int DM = 640, DQKV = 1920, DFF = 1728;
constexpr float LN_EPS = 1e-5f;
constexpr int SPIN_BUDGET = 1 << 20;
constexpr int REG_HELP = 56, REG_CONS = 224;

constexpr int NSLOT = 5, NITEMS_L = 30, NITEMS = 60;
constexpr int IT_WO = 9, IT_W1 = 13, IT_W2 = 21;
__host__ __device__ constexpr int slot_off(int k) { return k % 5 < 4 ? (k % 5) * 40960 : 3 * 40960 + 38912; }
constexpr int RING_BYTES = 3 * 40960 + 2 * 38912;
constexpr int STAGE_OFF = slot_off(3);

constexpr int OFF_XQM = RING_BYTES;
constexpr int OFF_XW1 = OFF_XQM + 3072;
constexpr int OFF_XQR = OFF_XW1 + 3584;
constexpr int XTRA_BYTES = 7424;
constexpr int OFF_PARK = OFF_XQM + XTRA_BYTES;
constexpr int OFF_RK = OFF_PARK + 8 * 2560;
constexpr int BAR_FULL = OFF_RK + 256, BAR_EMPTY = BAR_FULL + 40, BAR_STAGE = BAR_EMPTY + 40, BAR_CS = BAR_STAGE + 8, BAR_ORD = BAR_CS + 16;
constexpr int NORD = 7;
constexpr int BAR_X = BAR_ORD + NORD * 8;
constexpr int SMEM_BYTES = BAR_X + 16;
static_assert(SMEM_BYTES <= 232448 - 512, "smem");

constexpr int V_X = 0, V_O = 5, V_HB = 10, V_HA = 18, V_ST = 24, V_HALO = 25;
constexpr int WBOX = 5 * 512, RBOX = 8 * WBOX, PLANE = 8 * RBOX, BBOX = 9 * PLANE;
__host__ __device__ constexpr int voff(int v) { return v / 5 * PLANE + v % 5 * 512; }
constexpr uint32_t G_CS = 16 * BBOX;
constexpr uint32_t G_EPOCH = G_CS + 8 * 2 * 3 * 5120;
constexpr uint32_t G_BYTES = G_EPOCH + 128 * 128;
__device__ __align__(1024) uint4 g_scratch[G_BYTES / 16];

struct Params {
    char* scr;
    const __nv_bfloat16 *wqkv, *w1;
    int lcs;
    uint8_t role[64];
};

#define TL(slot) do {} while (0)
#define TLH(slot) do {} while (0)
#define TLDUMP(n) do {} while (0)
#define TLINIT
constexpr int SMEM_LAUNCH = SMEM_BYTES;

template <int N> struct IntC { static constexpr int value = N; };
__device__ __forceinline__ uint32_t smem_u32(const void* p) { return (uint32_t)__cvta_generic_to_shared(p); }
__device__ __forceinline__ int launder(int v) { asm volatile("" : "+r"(v)); return v; }
__device__ __forceinline__ bool elect_one() {
    uint32_t p;
    asm volatile("{.reg .pred q; elect.sync _|q, 0xffffffff; selp.u32 %0, 1, 0, q;}" : "=r"(p));
    return p;
}
__device__ __forceinline__ void mbar_init(uint32_t b, int c) { asm volatile("mbarrier.init.shared::cta.b64 [%0], %1;" :: "r"(b), "r"(c) : "memory"); }
__device__ __forceinline__ void mbar_expect(uint32_t b, int bytes) { asm volatile("mbarrier.arrive.expect_tx.shared::cta.b64 _, [%0], %1;" :: "r"(b), "r"(bytes) : "memory"); }
__device__ __forceinline__ void mbar_arrive(uint32_t b) { asm volatile("mbarrier.arrive.shared::cta.b64 _, [%0];" :: "r"(b) : "memory"); }
__device__ __forceinline__ void mbar_arrive_cluster(uint32_t b) { asm volatile("mbarrier.arrive.shared::cluster.b64 _, [%0];" :: "r"(b) : "memory"); }
__device__ __forceinline__ void mbar_wait(uint32_t b, uint32_t parity, int& budget) {
    uint32_t ok;
#pragma unroll 1
    do {
        asm volatile("{.reg .pred p; mbarrier.try_wait.parity.shared::cta.b64 p, [%1], %2; selp.u32 %0, 1, 0, p;}" : "=r"(ok) : "r"(b), "r"(parity) : "memory");
    } while (!ok && --budget >= 0);
}
__device__ __forceinline__ void ldv(uint32_t (&v)[4], const void* p) {
    asm volatile("{.reg .b128 t; ld.relaxed.gpu.global.b128 t, [%4]; mov.b128 {%0,%1,%2,%3}, t;}"
                 : "=r"(v[0]), "=r"(v[1]), "=r"(v[2]), "=r"(v[3]) : "l"(p) : "memory");
}
__device__ __forceinline__ void stv(void* p, uint32_t a, uint32_t b, uint32_t c, uint32_t d) {
    asm volatile("{.reg .b128 t; mov.b128 t, {%0,%1,%2,%3}; st.relaxed.gpu.global.b128 [%4], t;}"
                 :: "r"(a), "r"(b), "r"(c), "r"(d), "l"(p) : "memory");
}
__device__ __forceinline__ uint32_t tagged(uint32_t w, uint32_t tag) { return (w & ~1u) | tag; }
__device__ __forceinline__ uint32_t pack2(float lo, float hi) {
    uint32_t r; asm("cvt.rn.bf16x2.f32 %0, %1, %2;" : "=r"(r) : "f"(hi), "f"(lo)); return r;
}
__device__ __forceinline__ uint32_t pack2_relu(float lo, float hi) {
    uint32_t r; asm("cvt.rn.relu.bf16x2.f32 %0, %1, %2;" : "=r"(r) : "f"(hi), "f"(lo)); return r;
}
__device__ __forceinline__ float bf_lo(uint32_t w) { return __uint_as_float(w << 16); }
__device__ __forceinline__ float bf_hi(uint32_t w) { return __uint_as_float(w & 0xffff0000u); }
__device__ __forceinline__ uint32_t movm(uint32_t a) {
    uint32_t r; asm volatile("movmatrix.sync.aligned.m8n8.trans.b16 %0, %1;" : "=r"(r) : "r"(a)); return r;
}
__device__ __forceinline__ void ldsm4(uint32_t (&v)[4], uint32_t a) {
    asm volatile("ldmatrix.sync.aligned.m8n8.x4.shared.b16 {%0,%1,%2,%3}, [%4];" : "=r"(v[0]), "=r"(v[1]), "=r"(v[2]), "=r"(v[3]) : "r"(a) : "memory");
}
__device__ __forceinline__ void ldsm4t(uint32_t (&v)[4], uint32_t a) {
    asm volatile("ldmatrix.sync.aligned.m8n8.x4.trans.shared.b16 {%0,%1,%2,%3}, [%4];" : "=r"(v[0]), "=r"(v[1]), "=r"(v[2]), "=r"(v[3]) : "r"(a) : "memory");
}
__device__ __forceinline__ void stsm4(uint32_t a, uint32_t v0, uint32_t v1, uint32_t v2, uint32_t v3) {
    asm volatile("stmatrix.sync.aligned.m8n8.x4.shared.b16 [%0], {%1,%2,%3,%4};" :: "r"(a), "r"(v0), "r"(v1), "r"(v2), "r"(v3) : "memory");
}
__device__ __forceinline__ float ex2(float x) { float r; asm("ex2.approx.ftz.f32 %0, %1;" : "=f"(r) : "f"(x)); return r; }
__device__ __forceinline__ float rcp(float x) { float r; asm("rcp.approx.ftz.f32 %0, %1;" : "=f"(r) : "f"(x)); return r; }
__device__ __forceinline__ float rsq(float x) { float r; asm("rsqrt.approx.ftz.f32 %0, %1;" : "=f"(r) : "f"(x)); return r; }
__device__ __forceinline__ void mma_k8_init(float (&d)[4], uint32_t a0, uint32_t a1, uint32_t b0) {
    asm volatile("mma.sync.aligned.m16n8k8.row.col.f32.bf16.bf16.f32 {%0,%1,%2,%3}, {%4,%5}, {%6}, {%7,%7,%7,%7};"
                 : "=f"(d[0]), "=f"(d[1]), "=f"(d[2]), "=f"(d[3]) : "r"(a0), "r"(a1), "r"(b0), "f"(0.f));
}
__device__ __forceinline__ void mma_k16_acc(float (&d)[4], uint32_t a0, uint32_t a1, uint32_t a2, uint32_t a3, uint32_t b0, uint32_t b1) {
    asm volatile("mma.sync.aligned.m16n8k16.row.col.f32.bf16.bf16.f32 {%0,%1,%2,%3}, {%4,%5,%6,%7}, {%8,%9}, {%0,%1,%2,%3};"
                 : "+f"(d[0]), "+f"(d[1]), "+f"(d[2]), "+f"(d[3]) : "r"(a0), "r"(a1), "r"(a2), "r"(a3), "r"(b0), "r"(b1));
}
__device__ __forceinline__ void wg_fence() { asm volatile("wgmma.fence.sync.aligned;" ::: "memory"); }
__device__ __forceinline__ void wg_commit() { asm volatile("wgmma.commit_group.sync.aligned;" ::: "memory"); }
template <int N> __device__ __forceinline__ void wg_wait() { asm volatile("wgmma.wait_group.sync.aligned %0;" :: "n"(N) : "memory"); }
template <int N> __device__ __forceinline__ void reg_fence(float (&d)[N]) {
#pragma unroll
    for (int i = 0; i < N; i++) asm volatile("" : "+f"(d[i]) :: "memory");
}
template <int N, int OFF, int TOT> __device__ __forceinline__ void rename(float (&d)[N], const float (&s)[TOT]) {
#pragma unroll
    for (int i = 0; i < N; i++) asm volatile("mov.f32 %0, %1;" : "=f"(d[i]) : "f"(s[OFF + i]));
}
__device__ __forceinline__ uint64_t mkdesc(uint32_t a16, uint32_t off, uint32_t lbo, uint32_t sbo, int sw) {
    const uint32_t lo = a16 + ((off >> 4) + ((lbo >> 4) << 16));
    const uint32_t hi = (sbo >> 4) | ((uint32_t)sw << 30);
    return ((uint64_t)hi << 32) | lo;
}
__device__ __forceinline__ void tma2d_mc(uint32_t dst, const CUtensorMap* tm, int c0, int c1, uint32_t bar, uint16_t mask) {
    asm volatile("cp.async.bulk.tensor.2d.shared::cluster.global.mbarrier::complete_tx::bytes.multicast::cluster [%0], [%1, {%3, %4}], [%2], %5;"
                 :: "r"(dst), "l"(tm), "r"(bar), "r"(c0), "r"(c1), "h"(mask) : "memory");
}
__device__ __forceinline__ void tma2d(uint32_t dst, const CUtensorMap* tm, int c0, int c1, uint32_t bar) {
    asm volatile("cp.async.bulk.tensor.2d.shared::cluster.global.mbarrier::complete_tx::bytes [%0], [%1, {%3, %4}], [%2];"
                 :: "r"(dst), "l"(tm), "r"(bar), "r"(c0), "r"(c1) : "memory");
}
__device__ __forceinline__ void tma3d_mc(uint32_t dst, const CUtensorMap* tm, int c0, int c1, int c2, uint32_t bar, uint16_t mask) {
    asm volatile("cp.async.bulk.tensor.3d.shared::cluster.global.mbarrier::complete_tx::bytes.multicast::cluster [%0], [%1, {%3, %4, %5}], [%2], %6;"
                 :: "r"(dst), "l"(tm), "r"(bar), "r"(c0), "r"(c1), "r"(c2), "h"(mask) : "memory");
}
__device__ __forceinline__ void prefetch_map(const CUtensorMap* tm) { asm volatile("prefetch.tensormap [%0];" :: "l"(tm) : "memory"); }

__device__ __forceinline__ void wgmma_n192_acc(float (&d)[96], const uint32_t (&a)[4], uint64_t db) {
    asm volatile("{.reg .pred p; setp.eq.b32 p, 0, 0;\n"
        "wgmma.mma_async.sync.aligned.m64n192k16.f32.bf16.bf16 {"
        "%0, %1, %2, %3, %4, %5, %6, %7, %8, %9, %10, %11, %12, %13, %14, %15, %16, %17, %18, %19, %20, %21, %22, %23, "
        "%24, %25, %26, %27, %28, %29, %30, %31, %32, %33, %34, %35, %36, %37, %38, %39, %40, %41, %42, %43, %44, %45, %46, %47, "
        "%48, %49, %50, %51, %52, %53, %54, %55, %56, %57, %58, %59, %60, %61, %62, %63, %64, %65, %66, %67, %68, %69, %70, %71, "
        "%72, %73, %74, %75, %76, %77, %78, %79, %80, %81, %82, %83, %84, %85, %86, %87, %88, %89, %90, %91, %92, %93, %94, %95"
        "}, {%96, %97, %98, %99}, %100, p, 1, 1, 1;}\n"
        : "+f"(d[0]), "+f"(d[1]), "+f"(d[2]), "+f"(d[3]), "+f"(d[4]), "+f"(d[5]), "+f"(d[6]), "+f"(d[7]), "+f"(d[8]), "+f"(d[9]), "+f"(d[10]), "+f"(d[11]),
          "+f"(d[12]), "+f"(d[13]), "+f"(d[14]), "+f"(d[15]), "+f"(d[16]), "+f"(d[17]), "+f"(d[18]), "+f"(d[19]), "+f"(d[20]), "+f"(d[21]), "+f"(d[22]), "+f"(d[23]),
          "+f"(d[24]), "+f"(d[25]), "+f"(d[26]), "+f"(d[27]), "+f"(d[28]), "+f"(d[29]), "+f"(d[30]), "+f"(d[31]), "+f"(d[32]), "+f"(d[33]), "+f"(d[34]), "+f"(d[35]),
          "+f"(d[36]), "+f"(d[37]), "+f"(d[38]), "+f"(d[39]), "+f"(d[40]), "+f"(d[41]), "+f"(d[42]), "+f"(d[43]), "+f"(d[44]), "+f"(d[45]), "+f"(d[46]), "+f"(d[47]),
          "+f"(d[48]), "+f"(d[49]), "+f"(d[50]), "+f"(d[51]), "+f"(d[52]), "+f"(d[53]), "+f"(d[54]), "+f"(d[55]), "+f"(d[56]), "+f"(d[57]), "+f"(d[58]), "+f"(d[59]),
          "+f"(d[60]), "+f"(d[61]), "+f"(d[62]), "+f"(d[63]), "+f"(d[64]), "+f"(d[65]), "+f"(d[66]), "+f"(d[67]), "+f"(d[68]), "+f"(d[69]), "+f"(d[70]), "+f"(d[71]),
          "+f"(d[72]), "+f"(d[73]), "+f"(d[74]), "+f"(d[75]), "+f"(d[76]), "+f"(d[77]), "+f"(d[78]), "+f"(d[79]), "+f"(d[80]), "+f"(d[81]), "+f"(d[82]), "+f"(d[83]),
          "+f"(d[84]), "+f"(d[85]), "+f"(d[86]), "+f"(d[87]), "+f"(d[88]), "+f"(d[89]), "+f"(d[90]), "+f"(d[91]), "+f"(d[92]), "+f"(d[93]), "+f"(d[94]), "+f"(d[95])
        : "r"(a[0]), "r"(a[1]), "r"(a[2]), "r"(a[3]), "l"(db));
}
__device__ __forceinline__ void wgmma_n192_init(float (&d)[96], const uint32_t (&a)[4], uint64_t db) {
    asm volatile("{.reg .pred p; setp.ne.b32 p, 0, 0;\n"
        "wgmma.mma_async.sync.aligned.m64n192k16.f32.bf16.bf16 {"
        "%0, %1, %2, %3, %4, %5, %6, %7, %8, %9, %10, %11, %12, %13, %14, %15, %16, %17, %18, %19, %20, %21, %22, %23, "
        "%24, %25, %26, %27, %28, %29, %30, %31, %32, %33, %34, %35, %36, %37, %38, %39, %40, %41, %42, %43, %44, %45, %46, %47, "
        "%48, %49, %50, %51, %52, %53, %54, %55, %56, %57, %58, %59, %60, %61, %62, %63, %64, %65, %66, %67, %68, %69, %70, %71, "
        "%72, %73, %74, %75, %76, %77, %78, %79, %80, %81, %82, %83, %84, %85, %86, %87, %88, %89, %90, %91, %92, %93, %94, %95"
        "}, {%96, %97, %98, %99}, %100, p, 1, 1, 1;}\n"
        : "=f"(d[0]), "=f"(d[1]), "=f"(d[2]), "=f"(d[3]), "=f"(d[4]), "=f"(d[5]), "=f"(d[6]), "=f"(d[7]), "=f"(d[8]), "=f"(d[9]), "=f"(d[10]), "=f"(d[11]),
          "=f"(d[12]), "=f"(d[13]), "=f"(d[14]), "=f"(d[15]), "=f"(d[16]), "=f"(d[17]), "=f"(d[18]), "=f"(d[19]), "=f"(d[20]), "=f"(d[21]), "=f"(d[22]), "=f"(d[23]),
          "=f"(d[24]), "=f"(d[25]), "=f"(d[26]), "=f"(d[27]), "=f"(d[28]), "=f"(d[29]), "=f"(d[30]), "=f"(d[31]), "=f"(d[32]), "=f"(d[33]), "=f"(d[34]), "=f"(d[35]),
          "=f"(d[36]), "=f"(d[37]), "=f"(d[38]), "=f"(d[39]), "=f"(d[40]), "=f"(d[41]), "=f"(d[42]), "=f"(d[43]), "=f"(d[44]), "=f"(d[45]), "=f"(d[46]), "=f"(d[47]),
          "=f"(d[48]), "=f"(d[49]), "=f"(d[50]), "=f"(d[51]), "=f"(d[52]), "=f"(d[53]), "=f"(d[54]), "=f"(d[55]), "=f"(d[56]), "=f"(d[57]), "=f"(d[58]), "=f"(d[59]),
          "=f"(d[60]), "=f"(d[61]), "=f"(d[62]), "=f"(d[63]), "=f"(d[64]), "=f"(d[65]), "=f"(d[66]), "=f"(d[67]), "=f"(d[68]), "=f"(d[69]), "=f"(d[70]), "=f"(d[71]),
          "=f"(d[72]), "=f"(d[73]), "=f"(d[74]), "=f"(d[75]), "=f"(d[76]), "=f"(d[77]), "=f"(d[78]), "=f"(d[79]), "=f"(d[80]), "=f"(d[81]), "=f"(d[82]), "=f"(d[83]),
          "=f"(d[84]), "=f"(d[85]), "=f"(d[86]), "=f"(d[87]), "=f"(d[88]), "=f"(d[89]), "=f"(d[90]), "=f"(d[91]), "=f"(d[92]), "=f"(d[93]), "=f"(d[94]), "=f"(d[95])
        : "r"(a[0]), "r"(a[1]), "r"(a[2]), "r"(a[3]), "l"(db));
}
__device__ __forceinline__ void wgmma_n48_acc(float (&d)[24], const uint32_t (&a)[4], uint64_t db) {
    asm volatile("{.reg .pred p; setp.eq.b32 p, 0, 0;\n"
        "wgmma.mma_async.sync.aligned.m64n48k16.f32.bf16.bf16 {"
        "%0, %1, %2, %3, %4, %5, %6, %7, %8, %9, %10, %11, %12, %13, %14, %15, %16, %17, %18, %19, %20, %21, %22, %23"
        "}, {%24, %25, %26, %27}, %28, p, 1, 1, 1;}\n"
        : "+f"(d[0]), "+f"(d[1]), "+f"(d[2]), "+f"(d[3]), "+f"(d[4]), "+f"(d[5]), "+f"(d[6]), "+f"(d[7]), "+f"(d[8]), "+f"(d[9]), "+f"(d[10]), "+f"(d[11]),
          "+f"(d[12]), "+f"(d[13]), "+f"(d[14]), "+f"(d[15]), "+f"(d[16]), "+f"(d[17]), "+f"(d[18]), "+f"(d[19]), "+f"(d[20]), "+f"(d[21]), "+f"(d[22]), "+f"(d[23])
        : "r"(a[0]), "r"(a[1]), "r"(a[2]), "r"(a[3]), "l"(db));
}
__device__ __forceinline__ void wgmma_n48_init(float (&d)[24], const uint32_t (&a)[4], uint64_t db) {
    asm volatile("{.reg .pred p; setp.ne.b32 p, 0, 0;\n"
        "wgmma.mma_async.sync.aligned.m64n48k16.f32.bf16.bf16 {"
        "%0, %1, %2, %3, %4, %5, %6, %7, %8, %9, %10, %11, %12, %13, %14, %15, %16, %17, %18, %19, %20, %21, %22, %23"
        "}, {%24, %25, %26, %27}, %28, p, 1, 1, 1;}\n"
        : "=f"(d[0]), "=f"(d[1]), "=f"(d[2]), "=f"(d[3]), "=f"(d[4]), "=f"(d[5]), "=f"(d[6]), "=f"(d[7]), "=f"(d[8]), "=f"(d[9]), "=f"(d[10]), "=f"(d[11]),
          "=f"(d[12]), "=f"(d[13]), "=f"(d[14]), "=f"(d[15]), "=f"(d[16]), "=f"(d[17]), "=f"(d[18]), "=f"(d[19]), "=f"(d[20]), "=f"(d[21]), "=f"(d[22]), "=f"(d[23])
        : "r"(a[0]), "r"(a[1]), "r"(a[2]), "r"(a[3]), "l"(db));
}
__device__ __forceinline__ void wgmma_n224_acc(float (&d)[112], const uint32_t (&a)[4], uint64_t db) {
    asm volatile("{.reg .pred p; setp.eq.b32 p, 0, 0;\n"
        "wgmma.mma_async.sync.aligned.m64n224k16.f32.bf16.bf16 {"
        "%0, %1, %2, %3, %4, %5, %6, %7, %8, %9, %10, %11, %12, %13, %14, %15, %16, %17, %18, %19, %20, %21, %22, %23, "
        "%24, %25, %26, %27, %28, %29, %30, %31, %32, %33, %34, %35, %36, %37, %38, %39, %40, %41, %42, %43, %44, %45, %46, %47, "
        "%48, %49, %50, %51, %52, %53, %54, %55, %56, %57, %58, %59, %60, %61, %62, %63, %64, %65, %66, %67, %68, %69, %70, %71, "
        "%72, %73, %74, %75, %76, %77, %78, %79, %80, %81, %82, %83, %84, %85, %86, %87, %88, %89, %90, %91, %92, %93, %94, %95, "
        "%96, %97, %98, %99, %100, %101, %102, %103, %104, %105, %106, %107, %108, %109, %110, %111"
        "}, {%112, %113, %114, %115}, %116, p, 1, 1, 1;}\n"
        : "+f"(d[0]), "+f"(d[1]), "+f"(d[2]), "+f"(d[3]), "+f"(d[4]), "+f"(d[5]), "+f"(d[6]), "+f"(d[7]), "+f"(d[8]), "+f"(d[9]), "+f"(d[10]), "+f"(d[11]),
          "+f"(d[12]), "+f"(d[13]), "+f"(d[14]), "+f"(d[15]), "+f"(d[16]), "+f"(d[17]), "+f"(d[18]), "+f"(d[19]), "+f"(d[20]), "+f"(d[21]), "+f"(d[22]), "+f"(d[23]),
          "+f"(d[24]), "+f"(d[25]), "+f"(d[26]), "+f"(d[27]), "+f"(d[28]), "+f"(d[29]), "+f"(d[30]), "+f"(d[31]), "+f"(d[32]), "+f"(d[33]), "+f"(d[34]), "+f"(d[35]),
          "+f"(d[36]), "+f"(d[37]), "+f"(d[38]), "+f"(d[39]), "+f"(d[40]), "+f"(d[41]), "+f"(d[42]), "+f"(d[43]), "+f"(d[44]), "+f"(d[45]), "+f"(d[46]), "+f"(d[47]),
          "+f"(d[48]), "+f"(d[49]), "+f"(d[50]), "+f"(d[51]), "+f"(d[52]), "+f"(d[53]), "+f"(d[54]), "+f"(d[55]), "+f"(d[56]), "+f"(d[57]), "+f"(d[58]), "+f"(d[59]),
          "+f"(d[60]), "+f"(d[61]), "+f"(d[62]), "+f"(d[63]), "+f"(d[64]), "+f"(d[65]), "+f"(d[66]), "+f"(d[67]), "+f"(d[68]), "+f"(d[69]), "+f"(d[70]), "+f"(d[71]),
          "+f"(d[72]), "+f"(d[73]), "+f"(d[74]), "+f"(d[75]), "+f"(d[76]), "+f"(d[77]), "+f"(d[78]), "+f"(d[79]), "+f"(d[80]), "+f"(d[81]), "+f"(d[82]), "+f"(d[83]),
          "+f"(d[84]), "+f"(d[85]), "+f"(d[86]), "+f"(d[87]), "+f"(d[88]), "+f"(d[89]), "+f"(d[90]), "+f"(d[91]), "+f"(d[92]), "+f"(d[93]), "+f"(d[94]), "+f"(d[95]),
          "+f"(d[96]), "+f"(d[97]), "+f"(d[98]), "+f"(d[99]), "+f"(d[100]), "+f"(d[101]), "+f"(d[102]), "+f"(d[103]), "+f"(d[104]), "+f"(d[105]), "+f"(d[106]), "+f"(d[107]),
          "+f"(d[108]), "+f"(d[109]), "+f"(d[110]), "+f"(d[111])
        : "r"(a[0]), "r"(a[1]), "r"(a[2]), "r"(a[3]), "l"(db));
}
__device__ __forceinline__ void wgmma_n224_init(float (&d)[112], const uint32_t (&a)[4], uint64_t db) {
    asm volatile("{.reg .pred p; setp.ne.b32 p, 0, 0;\n"
        "wgmma.mma_async.sync.aligned.m64n224k16.f32.bf16.bf16 {"
        "%0, %1, %2, %3, %4, %5, %6, %7, %8, %9, %10, %11, %12, %13, %14, %15, %16, %17, %18, %19, %20, %21, %22, %23, "
        "%24, %25, %26, %27, %28, %29, %30, %31, %32, %33, %34, %35, %36, %37, %38, %39, %40, %41, %42, %43, %44, %45, %46, %47, "
        "%48, %49, %50, %51, %52, %53, %54, %55, %56, %57, %58, %59, %60, %61, %62, %63, %64, %65, %66, %67, %68, %69, %70, %71, "
        "%72, %73, %74, %75, %76, %77, %78, %79, %80, %81, %82, %83, %84, %85, %86, %87, %88, %89, %90, %91, %92, %93, %94, %95, "
        "%96, %97, %98, %99, %100, %101, %102, %103, %104, %105, %106, %107, %108, %109, %110, %111"
        "}, {%112, %113, %114, %115}, %116, p, 1, 1, 1;}\n"
        : "=f"(d[0]), "=f"(d[1]), "=f"(d[2]), "=f"(d[3]), "=f"(d[4]), "=f"(d[5]), "=f"(d[6]), "=f"(d[7]), "=f"(d[8]), "=f"(d[9]), "=f"(d[10]), "=f"(d[11]),
          "=f"(d[12]), "=f"(d[13]), "=f"(d[14]), "=f"(d[15]), "=f"(d[16]), "=f"(d[17]), "=f"(d[18]), "=f"(d[19]), "=f"(d[20]), "=f"(d[21]), "=f"(d[22]), "=f"(d[23]),
          "=f"(d[24]), "=f"(d[25]), "=f"(d[26]), "=f"(d[27]), "=f"(d[28]), "=f"(d[29]), "=f"(d[30]), "=f"(d[31]), "=f"(d[32]), "=f"(d[33]), "=f"(d[34]), "=f"(d[35]),
          "=f"(d[36]), "=f"(d[37]), "=f"(d[38]), "=f"(d[39]), "=f"(d[40]), "=f"(d[41]), "=f"(d[42]), "=f"(d[43]), "=f"(d[44]), "=f"(d[45]), "=f"(d[46]), "=f"(d[47]),
          "=f"(d[48]), "=f"(d[49]), "=f"(d[50]), "=f"(d[51]), "=f"(d[52]), "=f"(d[53]), "=f"(d[54]), "=f"(d[55]), "=f"(d[56]), "=f"(d[57]), "=f"(d[58]), "=f"(d[59]),
          "=f"(d[60]), "=f"(d[61]), "=f"(d[62]), "=f"(d[63]), "=f"(d[64]), "=f"(d[65]), "=f"(d[66]), "=f"(d[67]), "=f"(d[68]), "=f"(d[69]), "=f"(d[70]), "=f"(d[71]),
          "=f"(d[72]), "=f"(d[73]), "=f"(d[74]), "=f"(d[75]), "=f"(d[76]), "=f"(d[77]), "=f"(d[78]), "=f"(d[79]), "=f"(d[80]), "=f"(d[81]), "=f"(d[82]), "=f"(d[83]),
          "=f"(d[84]), "=f"(d[85]), "=f"(d[86]), "=f"(d[87]), "=f"(d[88]), "=f"(d[89]), "=f"(d[90]), "=f"(d[91]), "=f"(d[92]), "=f"(d[93]), "=f"(d[94]), "=f"(d[95]),
          "=f"(d[96]), "=f"(d[97]), "=f"(d[98]), "=f"(d[99]), "=f"(d[100]), "=f"(d[101]), "=f"(d[102]), "=f"(d[103]), "=f"(d[104]), "=f"(d[105]), "=f"(d[106]), "=f"(d[107]),
          "=f"(d[108]), "=f"(d[109]), "=f"(d[110]), "=f"(d[111])
        : "r"(a[0]), "r"(a[1]), "r"(a[2]), "r"(a[3]), "l"(db));
}
__device__ __forceinline__ void wgmma_n80_acc(float (&d)[40], const uint32_t (&a)[4], uint64_t db) {
    asm volatile("{.reg .pred p; setp.eq.b32 p, 0, 0;\n"
        "wgmma.mma_async.sync.aligned.m64n80k16.f32.bf16.bf16 {"
        "%0, %1, %2, %3, %4, %5, %6, %7, %8, %9, %10, %11, %12, %13, %14, %15, %16, %17, %18, %19, %20, %21, %22, %23, "
        "%24, %25, %26, %27, %28, %29, %30, %31, %32, %33, %34, %35, %36, %37, %38, %39"
        "}, {%40, %41, %42, %43}, %44, p, 1, 1, 1;}\n"
        : "+f"(d[0]), "+f"(d[1]), "+f"(d[2]), "+f"(d[3]), "+f"(d[4]), "+f"(d[5]), "+f"(d[6]), "+f"(d[7]), "+f"(d[8]), "+f"(d[9]), "+f"(d[10]), "+f"(d[11]),
          "+f"(d[12]), "+f"(d[13]), "+f"(d[14]), "+f"(d[15]), "+f"(d[16]), "+f"(d[17]), "+f"(d[18]), "+f"(d[19]), "+f"(d[20]), "+f"(d[21]), "+f"(d[22]), "+f"(d[23]),
          "+f"(d[24]), "+f"(d[25]), "+f"(d[26]), "+f"(d[27]), "+f"(d[28]), "+f"(d[29]), "+f"(d[30]), "+f"(d[31]), "+f"(d[32]), "+f"(d[33]), "+f"(d[34]), "+f"(d[35]),
          "+f"(d[36]), "+f"(d[37]), "+f"(d[38]), "+f"(d[39])
        : "r"(a[0]), "r"(a[1]), "r"(a[2]), "r"(a[3]), "l"(db));
}
__device__ __forceinline__ void wgmma_n160_acc(float (&d)[80], const uint32_t (&a)[4], uint64_t db) {
    asm volatile("{.reg .pred p; setp.eq.b32 p, 0, 0;\n"
        "wgmma.mma_async.sync.aligned.m64n160k16.f32.bf16.bf16 {"
        "%0, %1, %2, %3, %4, %5, %6, %7, %8, %9, %10, %11, %12, %13, %14, %15, %16, %17, %18, %19, %20, %21, %22, %23, "
        "%24, %25, %26, %27, %28, %29, %30, %31, %32, %33, %34, %35, %36, %37, %38, %39, %40, %41, %42, %43, %44, %45, %46, %47, "
        "%48, %49, %50, %51, %52, %53, %54, %55, %56, %57, %58, %59, %60, %61, %62, %63, %64, %65, %66, %67, %68, %69, %70, %71, "
        "%72, %73, %74, %75, %76, %77, %78, %79"
        "}, {%80, %81, %82, %83}, %84, p, 1, 1, 1;}\n"
        : "+f"(d[0]), "+f"(d[1]), "+f"(d[2]), "+f"(d[3]), "+f"(d[4]), "+f"(d[5]), "+f"(d[6]), "+f"(d[7]), "+f"(d[8]), "+f"(d[9]), "+f"(d[10]), "+f"(d[11]),
          "+f"(d[12]), "+f"(d[13]), "+f"(d[14]), "+f"(d[15]), "+f"(d[16]), "+f"(d[17]), "+f"(d[18]), "+f"(d[19]), "+f"(d[20]), "+f"(d[21]), "+f"(d[22]), "+f"(d[23]),
          "+f"(d[24]), "+f"(d[25]), "+f"(d[26]), "+f"(d[27]), "+f"(d[28]), "+f"(d[29]), "+f"(d[30]), "+f"(d[31]), "+f"(d[32]), "+f"(d[33]), "+f"(d[34]), "+f"(d[35]),
          "+f"(d[36]), "+f"(d[37]), "+f"(d[38]), "+f"(d[39]), "+f"(d[40]), "+f"(d[41]), "+f"(d[42]), "+f"(d[43]), "+f"(d[44]), "+f"(d[45]), "+f"(d[46]), "+f"(d[47]),
          "+f"(d[48]), "+f"(d[49]), "+f"(d[50]), "+f"(d[51]), "+f"(d[52]), "+f"(d[53]), "+f"(d[54]), "+f"(d[55]), "+f"(d[56]), "+f"(d[57]), "+f"(d[58]), "+f"(d[59]),
          "+f"(d[60]), "+f"(d[61]), "+f"(d[62]), "+f"(d[63]), "+f"(d[64]), "+f"(d[65]), "+f"(d[66]), "+f"(d[67]), "+f"(d[68]), "+f"(d[69]), "+f"(d[70]), "+f"(d[71]),
          "+f"(d[72]), "+f"(d[73]), "+f"(d[74]), "+f"(d[75]), "+f"(d[76]), "+f"(d[77]), "+f"(d[78]), "+f"(d[79])
        : "r"(a[0]), "r"(a[1]), "r"(a[2]), "r"(a[3]), "l"(db));
}
__device__ __forceinline__ void wgmma_n160_init(float (&d)[80], const uint32_t (&a)[4], uint64_t db) {
    asm volatile("{.reg .pred p; setp.ne.b32 p, 0, 0;\n"
        "wgmma.mma_async.sync.aligned.m64n160k16.f32.bf16.bf16 {"
        "%0, %1, %2, %3, %4, %5, %6, %7, %8, %9, %10, %11, %12, %13, %14, %15, %16, %17, %18, %19, %20, %21, %22, %23, "
        "%24, %25, %26, %27, %28, %29, %30, %31, %32, %33, %34, %35, %36, %37, %38, %39, %40, %41, %42, %43, %44, %45, %46, %47, "
        "%48, %49, %50, %51, %52, %53, %54, %55, %56, %57, %58, %59, %60, %61, %62, %63, %64, %65, %66, %67, %68, %69, %70, %71, "
        "%72, %73, %74, %75, %76, %77, %78, %79"
        "}, {%80, %81, %82, %83}, %84, p, 1, 1, 1;}\n"
        : "=f"(d[0]), "=f"(d[1]), "=f"(d[2]), "=f"(d[3]), "=f"(d[4]), "=f"(d[5]), "=f"(d[6]), "=f"(d[7]), "=f"(d[8]), "=f"(d[9]), "=f"(d[10]), "=f"(d[11]),
          "=f"(d[12]), "=f"(d[13]), "=f"(d[14]), "=f"(d[15]), "=f"(d[16]), "=f"(d[17]), "=f"(d[18]), "=f"(d[19]), "=f"(d[20]), "=f"(d[21]), "=f"(d[22]), "=f"(d[23]),
          "=f"(d[24]), "=f"(d[25]), "=f"(d[26]), "=f"(d[27]), "=f"(d[28]), "=f"(d[29]), "=f"(d[30]), "=f"(d[31]), "=f"(d[32]), "=f"(d[33]), "=f"(d[34]), "=f"(d[35]),
          "=f"(d[36]), "=f"(d[37]), "=f"(d[38]), "=f"(d[39]), "=f"(d[40]), "=f"(d[41]), "=f"(d[42]), "=f"(d[43]), "=f"(d[44]), "=f"(d[45]), "=f"(d[46]), "=f"(d[47]),
          "=f"(d[48]), "=f"(d[49]), "=f"(d[50]), "=f"(d[51]), "=f"(d[52]), "=f"(d[53]), "=f"(d[54]), "=f"(d[55]), "=f"(d[56]), "=f"(d[57]), "=f"(d[58]), "=f"(d[59]),
          "=f"(d[60]), "=f"(d[61]), "=f"(d[62]), "=f"(d[63]), "=f"(d[64]), "=f"(d[65]), "=f"(d[66]), "=f"(d[67]), "=f"(d[68]), "=f"(d[69]), "=f"(d[70]), "=f"(d[71]),
          "=f"(d[72]), "=f"(d[73]), "=f"(d[74]), "=f"(d[75]), "=f"(d[76]), "=f"(d[77]), "=f"(d[78]), "=f"(d[79])
        : "r"(a[0]), "r"(a[1]), "r"(a[2]), "r"(a[3]), "l"(db));
}
__device__ __forceinline__ void wgmma_n128_acc(float (&d)[64], const uint32_t (&a)[4], uint64_t db) {
    asm volatile("{.reg .pred p; setp.eq.b32 p, 0, 0;\n"
        "wgmma.mma_async.sync.aligned.m64n128k16.f32.bf16.bf16 {"
        "%0, %1, %2, %3, %4, %5, %6, %7, %8, %9, %10, %11, %12, %13, %14, %15, %16, %17, %18, %19, %20, %21, %22, %23, "
        "%24, %25, %26, %27, %28, %29, %30, %31, %32, %33, %34, %35, %36, %37, %38, %39, %40, %41, %42, %43, %44, %45, %46, %47, "
        "%48, %49, %50, %51, %52, %53, %54, %55, %56, %57, %58, %59, %60, %61, %62, %63"
        "}, {%64, %65, %66, %67}, %68, p, 1, 1, 1;}\n"
        : "+f"(d[0]), "+f"(d[1]), "+f"(d[2]), "+f"(d[3]), "+f"(d[4]), "+f"(d[5]), "+f"(d[6]), "+f"(d[7]), "+f"(d[8]), "+f"(d[9]), "+f"(d[10]), "+f"(d[11]),
          "+f"(d[12]), "+f"(d[13]), "+f"(d[14]), "+f"(d[15]), "+f"(d[16]), "+f"(d[17]), "+f"(d[18]), "+f"(d[19]), "+f"(d[20]), "+f"(d[21]), "+f"(d[22]), "+f"(d[23]),
          "+f"(d[24]), "+f"(d[25]), "+f"(d[26]), "+f"(d[27]), "+f"(d[28]), "+f"(d[29]), "+f"(d[30]), "+f"(d[31]), "+f"(d[32]), "+f"(d[33]), "+f"(d[34]), "+f"(d[35]),
          "+f"(d[36]), "+f"(d[37]), "+f"(d[38]), "+f"(d[39]), "+f"(d[40]), "+f"(d[41]), "+f"(d[42]), "+f"(d[43]), "+f"(d[44]), "+f"(d[45]), "+f"(d[46]), "+f"(d[47]),
          "+f"(d[48]), "+f"(d[49]), "+f"(d[50]), "+f"(d[51]), "+f"(d[52]), "+f"(d[53]), "+f"(d[54]), "+f"(d[55]), "+f"(d[56]), "+f"(d[57]), "+f"(d[58]), "+f"(d[59]),
          "+f"(d[60]), "+f"(d[61]), "+f"(d[62]), "+f"(d[63])
        : "r"(a[0]), "r"(a[1]), "r"(a[2]), "r"(a[3]), "l"(db));
}
__device__ __forceinline__ void wgmma_n96_acc(float (&d)[48], const uint32_t (&a)[4], uint64_t db) {
    asm volatile("{.reg .pred p; setp.eq.b32 p, 0, 0;\n"
        "wgmma.mma_async.sync.aligned.m64n96k16.f32.bf16.bf16 {"
        "%0, %1, %2, %3, %4, %5, %6, %7, %8, %9, %10, %11, %12, %13, %14, %15, %16, %17, %18, %19, %20, %21, %22, %23, "
        "%24, %25, %26, %27, %28, %29, %30, %31, %32, %33, %34, %35, %36, %37, %38, %39, %40, %41, %42, %43, %44, %45, %46, %47"
        "}, {%48, %49, %50, %51}, %52, p, 1, 1, 1;}\n"
        : "+f"(d[0]), "+f"(d[1]), "+f"(d[2]), "+f"(d[3]), "+f"(d[4]), "+f"(d[5]), "+f"(d[6]), "+f"(d[7]), "+f"(d[8]), "+f"(d[9]), "+f"(d[10]), "+f"(d[11]),
          "+f"(d[12]), "+f"(d[13]), "+f"(d[14]), "+f"(d[15]), "+f"(d[16]), "+f"(d[17]), "+f"(d[18]), "+f"(d[19]), "+f"(d[20]), "+f"(d[21]), "+f"(d[22]), "+f"(d[23]),
          "+f"(d[24]), "+f"(d[25]), "+f"(d[26]), "+f"(d[27]), "+f"(d[28]), "+f"(d[29]), "+f"(d[30]), "+f"(d[31]), "+f"(d[32]), "+f"(d[33]), "+f"(d[34]), "+f"(d[35]),
          "+f"(d[36]), "+f"(d[37]), "+f"(d[38]), "+f"(d[39]), "+f"(d[40]), "+f"(d[41]), "+f"(d[42]), "+f"(d[43]), "+f"(d[44]), "+f"(d[45]), "+f"(d[46]), "+f"(d[47])
        : "r"(a[0]), "r"(a[1]), "r"(a[2]), "r"(a[3]), "l"(db));
}
__device__ __forceinline__ void wgmma_n64_acc(float (&d)[32], const uint32_t (&a)[4], uint64_t db) {
    asm volatile("{.reg .pred p; setp.eq.b32 p, 0, 0;\n"
        "wgmma.mma_async.sync.aligned.m64n64k16.f32.bf16.bf16 {"
        "%0, %1, %2, %3, %4, %5, %6, %7, %8, %9, %10, %11, %12, %13, %14, %15, %16, %17, %18, %19, %20, %21, %22, %23, "
        "%24, %25, %26, %27, %28, %29, %30, %31"
        "}, {%32, %33, %34, %35}, %36, p, 1, 1, 1;}\n"
        : "+f"(d[0]), "+f"(d[1]), "+f"(d[2]), "+f"(d[3]), "+f"(d[4]), "+f"(d[5]), "+f"(d[6]), "+f"(d[7]), "+f"(d[8]), "+f"(d[9]), "+f"(d[10]), "+f"(d[11]),
          "+f"(d[12]), "+f"(d[13]), "+f"(d[14]), "+f"(d[15]), "+f"(d[16]), "+f"(d[17]), "+f"(d[18]), "+f"(d[19]), "+f"(d[20]), "+f"(d[21]), "+f"(d[22]), "+f"(d[23]),
          "+f"(d[24]), "+f"(d[25]), "+f"(d[26]), "+f"(d[27]), "+f"(d[28]), "+f"(d[29]), "+f"(d[30]), "+f"(d[31])
        : "r"(a[0]), "r"(a[1]), "r"(a[2]), "r"(a[3]), "l"(db));
}

__device__ __forceinline__ int slice_at(int t, int r) { return t < 2 ? r ^ t : (t - 2) + ((t - 2) >= (r & 6) ? 2 : 0); }
__device__ __forceinline__ int main_col(int j) { return 80 * j + 16 * (j & 1); }
__device__ __forceinline__ int rem_col(int j) { return 80 * j + 64 - 64 * (j & 1); }
__device__ __forceinline__ int kstep(int odd, int u) { return u < 4 ? odd + u : 4 - 4 * odd; }
__device__ __forceinline__ int hsrc_at(int t, int r) {
    if (t < 2) return r;
    const int i = t < 5 ? t - 2 : t - 5;
    return 2 * (i + (i >= (r >> 1) ? 1 : 0)) + (r & 1);
}
__device__ __forceinline__ constexpr bool hpartB(int t) { return t == 1 || t >= 5; }

template <int NV> __device__ __forceinline__ bool bad_vecs(const uint32_t (&v)[NV][4], uint32_t tag) {
    uint32_t bad = 0;
#pragma unroll
    for (int u = 0; u < NV; u += 2) {
        if (u + 1 < NV) {
            uint32_t x;
            asm("lop3.b32 %0, %1, %2, %3, 0x7e;" : "=r"(x) : "r"(v[u][0]), "r"(v[u + 1][0]), "r"(tag));
            if (u == 0) bad = x; else asm("or.b32 %0, %0, %1;" : "+r"(bad) : "r"(x));
        } else {
            asm("lop3.b32 %0, %1, %2, %0, 0xbe;" : "+r"(bad) : "r"(v[u][0]), "r"(tag));
        }
    }
    return __any_sync(0xffffffffu, bad & 1);
}

struct Ctx {
    uint32_t sb, sb16;
    uint32_t rel_addr;
    char* mb;
    int r, warp, layer;
    int budget;
    uint32_t eall;
    __device__ __forceinline__ uint32_t lane16() const { return launder((uint32_t)(size_t)mb) & 511; }
    __device__ __forceinline__ int lane() const { return lane16() >> 4; }
    __device__ __forceinline__ uint32_t park() const { return sb + OFF_PARK + warp * 2560 + lane16(); }
    __device__ __forceinline__ const char* box(int src) const { return mb + launder(src - r) * RBOX; }
};
__device__ __forceinline__ void sched_fence(Ctx& c) {
    asm volatile("{.reg .pred p; setp.eq.s32 p, %0, 0x400000%=;\nFENCE_%=: @p nanosleep.u32 1; @p bra.uni FENCE_%=;}" :: "r"(c.eall) : "memory");
}
__device__ __forceinline__ void wait_full(Ctx& c, int k) { mbar_wait(c.sb + BAR_FULL + (k % NSLOT) * 8, (k / NSLOT) & 1, c.budget); }
__device__ __forceinline__ void release(const Ctx& c, int k) {
    if (c.rel_addr != 0 && (k < NITEMS_L - NSLOT || c.layer == 0)) mbar_arrive_cluster(c.rel_addr + (k % NSLOT) * 8);
}
template <int K> __device__ __forceinline__ void order_wait(Ctx& c) {
    if (((ORDER >> K) & 1) && c.warp >= 4) mbar_wait(c.sb + BAR_ORD + K * 8, c.layer, c.budget);
}
template <int K> __device__ __forceinline__ void order_post(const Ctx& c) {
    if (((ORDER >> K) & 1) && c.warp == 0 && c.rel_addr != 0) mbar_arrive(c.sb + BAR_ORD + K * 8);
}
template <int K, int FROM> __device__ __forceinline__ void gate_wait(Ctx& c) {
    if (((ORDER >> K) & 1) && (c.warp >> 2) != FROM) mbar_wait(c.sb + BAR_ORD + K * 8, c.layer, c.budget);
}
template <int K, int FROM> __device__ __forceinline__ void gate_post(const Ctx& c) {
    if (((ORDER >> K) & 1) && (c.warp >> 2) == FROM && c.rel_addr != 0) mbar_arrive(c.sb + BAR_ORD + K * 8);
}
template <int NV> __device__ __forceinline__ void ld_vecs(uint32_t (&v)[NV][4], const char* p, int v0) {
#pragma unroll
    for (int u = 0; u < NV; u++) ldv(v[u], p + voff(v0 + u));
}
template <int NV> __device__ __forceinline__ void publish(const Ctx& c, uint32_t (&v)[NV][4], int v0, uint32_t tag) {
#pragma unroll
    for (int u = 0; u < NV; u++) {
        v[u][0] = launder(tagged(v[u][0], tag));
        stv(c.mb + voff(v0 + u), v[u][0], v[u][1], v[u][2], v[u][3]);
    }
}
template <int NV, class F> __device__ __forceinline__ void check_vecs(Ctx& c, uint32_t (&v)[NV][4], uint32_t tag, F reload) {
    while (bad_vecs(v, tag) && --c.budget >= 0) reload();
}

__device__ __forceinline__ void probe(Ctx& c, int src, int vec) {
    const char* pp = c.mb + ((src - c.r) * RBOX - (int)c.lane16() + voff(vec) + 496);
    uint32_t v;
    do {
        asm volatile("ld.relaxed.gpu.global.u32 %0, [%1];" : "=r"(v) : "l"(pp) : "memory");
    } while (__any_sync(0xffffffffu, !(v & 1u)) && --c.budget >= 0);
}

__device__ __forceinline__ void park_x(const Ctx& c, const uint32_t (&v)[5][4]) {
    const uint32_t a = c.park();
#pragma unroll
    for (int u = 0; u < 5; u++) stsm4(a + u * 512, v[u][0], v[u][1], v[u][2], v[u][3]);
}
__device__ __forceinline__ void unpark_x(const Ctx& c, uint32_t (&v)[5][4]) {
    const uint32_t a = c.park();
#pragma unroll
    for (int u = 0; u < 5; u++) ldsm4(v[u], a + u * 512);
}
__device__ __forceinline__ void unstage(Ctx& c, uint32_t (&v)[5][4], int odd, int which) {
    const int lane = c.lane();
    const uint32_t a = c.sb + STAGE_OFF + which * 20480 + (c.warp * 16 + (lane & 15)) * 160 + (lane >> 4) * 16;
    mbar_wait(c.sb + BAR_X + which * 8, 0, c.budget);
#pragma unroll
    for (int u = 0; u < 5; u++) ldsm4(v[u], u < 4 ? a + odd * 32 + u * 32 : a + 128 - odd * 128);
}
__device__ __forceinline__ void pack_x(uint32_t (&X)[5][4], const float (&v)[40]) {
#pragma unroll
    for (int u = 0; u < 5; u++)
#pragma unroll
        for (int i = 0; i < 4; i++) X[u][i] = pack2(v[8 * u + 2 * i], v[8 * u + 2 * i + 1]);
}
__device__ __forceinline__ void unpack_x(float (&v)[40], const uint32_t (&X)[5][4]) {
#pragma unroll
    for (int u = 0; u < 5; u++)
#pragma unroll
        for (int i = 0; i < 4; i++) { v[8 * u + 2 * i] = bf_lo(X[u][i]); v[8 * u + 2 * i + 1] = bf_hi(X[u][i]); }
}
__device__ __forceinline__ void store_out(const Ctx& c, const uint32_t (&X)[5][4], const CUtensorMap* tm, int blk) {
    const int lane = c.lane(), odd = c.r & 1;
    const uint32_t tile = c.sb + OFF_PARK + c.warp * 2560;
    const uint32_t a = tile + (lane & 15) * 160 + (lane >> 4) * 16;
#pragma unroll
    for (int u = 0; u < 5; u++) stsm4(u < 4 ? a + odd * 32 + u * 32 : a + 128 - odd * 128, X[u][0], X[u][1], X[u][2], X[u][3]);
    asm volatile("fence.proxy.async.shared::cta;" ::: "memory");
    __syncwarp();
    if (elect_one()) {
        asm volatile("cp.async.bulk.tensor.2d.global.shared::cta.bulk_group [%0, {%2, %3}], [%1];"
                     :: "l"(tm), "r"(tile), "r"(640 * (c.warp >> 2) + 80 * c.r), "r"(64 * blk + 16 * (c.warp & 3)) : "memory");
        asm volatile("cp.async.bulk.commit_group;" ::: "memory");
        asm volatile("cp.async.bulk.wait_group 0;" ::: "memory");
    }
    __syncwarp();
}

template <int NB, int V0, uint32_t TAG> struct Gather {
    uint32_t buf[NB][5][4];
    __device__ __forceinline__ uint32_t (&at(int t))[5][4] { return buf[(t - 1) % NB]; }
    __device__ __forceinline__ void fetch(Ctx& c, int t) { ld_vecs(at(t), c.box(slice_at(t, c.r)), V0); }
    __device__ __forceinline__ void check(Ctx& c, int t) { check_vecs(c, at(t), TAG, [&]() { fetch(c, t); }); }
};

struct GQKV {
    float m[96], r[24];
    template <bool INIT> __device__ __forceinline__ void step(const uint32_t (&a)[5][4], uint32_t sb16, int off, int odd) {
#pragma unroll
        for (int u = 0; u < 5; u++) {
            const uint64_t dm = mkdesc(sb16 + kstep(odd, u) * 128, off, 10240, 1024, 1), dr = mkdesc(sb16 + kstep(odd, u) * 32, off + 30720, 2560, 256, 3);
            if (INIT && u == 0) { wgmma_n192_init(m, a[u], dm); wgmma_n48_init(r, a[u], dr); }
            else { wgmma_n192_acc(m, a[u], dm); wgmma_n48_acc(r, a[u], dr); }
        }
    }
};
struct GW1 {
    float m[112];
    template <bool INIT> __device__ __forceinline__ void step(const uint32_t (&a)[5][4], uint32_t sb16, int off, int odd) {
#pragma unroll
        for (int u = 0; u < 5; u++) {
            const uint64_t d = mkdesc(sb16 + kstep(odd, u) * 64, off, 5120, 512, 2);
            if (INIT && u == 0) wgmma_n224_init(m, a[u], d); else wgmma_n224_acc(m, a[u], d);
        }
    }
};

template <int K0, int LAST, uint32_t TAG, class G, class A, class Hook>
__device__ __forceinline__ void ln_head(G& g, A& a, Ctx& c, const uint32_t (&own)[5][4], const float (&xv)[40],
                                        float& rsA, float& rsB, uint32_t (&ax)[4], Hook hook, int tl0) {
    sched_fence(c);
    wg_fence();
    g.template step<true>(own, c.sb16, slot_off(K0), c.r & 1);
    wg_commit();
    if (tl0) TL(tl0 + 1);
    sched_fence(c);
    float s[4] = {0.f, 0.f, 0.f, 0.f};
#pragma unroll
    for (int j = 0; j < 10; j++) {
        s[0] += xv[4 * j] + xv[4 * j + 1];
        s[1] = fmaf(xv[4 * j], xv[4 * j], fmaf(xv[4 * j + 1], xv[4 * j + 1], s[1]));
        s[2] += xv[4 * j + 2] + xv[4 * j + 3];
        s[3] = fmaf(xv[4 * j + 2], xv[4 * j + 2], fmaf(xv[4 * j + 3], xv[4 * j + 3], s[3]));
    }
    reg_fence(s);
    wait_full(c, K0 + 1);
    hook(-1);
    a.check(c, 1);
    a.fetch(c, 2);
    uint32_t sv[2][4];
    auto sfetch = [&]() {
        const int lane = c.lane();
        const char* p = c.mb + (((lane & 3) - c.r) * RBOX + (lane >> 2) * 16 - lane * 16);
        ldv(sv[0], p + voff(V_ST)); ldv(sv[1], p + voff(V_ST) + 4 * RBOX);
    };
#pragma unroll
    for (int t = 1; t <= LAST; t++) {
        sched_fence(c);
        if (tl0) TL(tl0 + 2 + t);
        wg_fence();
        g.template step<false>(a.at(t), c.sb16, slot_off(K0 + t), t == 1 ? (c.r & 1) ^ 1 : t & 1);
        wg_commit();
        wg_wait<1>();
        release(c, K0 + t - 1);
        wait_full(c, K0 + t + 1);
        if (t == 1) {
#pragma unroll
            for (int i = 0; i < 4; i++) {
                s[i] += __shfl_xor_sync(0xffffffffu, s[i], 1);
                s[i] += __shfl_xor_sync(0xffffffffu, s[i], 2);
            }
            const int lane = c.lane();
            if ((lane & 3) == 0)
                stv(c.mb + voff(V_ST) - lane * 12, tagged(__float_as_uint(s[0]), TAG), __float_as_uint(s[1]), __float_as_uint(s[2]), __float_as_uint(s[3]));
            sched_fence(c);
        }
        a.check(c, t + 1);
        if (t == LAST) check_vecs(c, sv, TAG, sfetch);
        a.fetch(c, t + 2);
        if (t == LAST - 1) sfetch();
        hook(t);
    }
#pragma unroll
    for (int i = 0; i < 4; i++) {
        s[i] = __uint_as_float(sv[0][i]) + __uint_as_float(sv[1][i]);
        s[i] += __shfl_xor_sync(0xffffffffu, s[i], 1);
        s[i] += __shfl_xor_sync(0xffffffffu, s[i], 2);
    }
    const float mA = s[0] * (1.f / DM), mB = s[2] * (1.f / DM);
    rsA = rsq(fmaxf(fmaf(-mA, mA, s[1] * (1.f / DM)), 0.f) + LN_EPS);
    rsB = rsq(fmaxf(fmaf(-mB, mB, s[3] * (1.f / DM)), 0.f) + LN_EPS);
    const uint32_t h = pack2(mA, mB);
    const uint32_t l = pack2(mA - bf_lo(h), mB - bf_hi(h));
    const bool on = (c.lane16() & 32) == 0;
    ax[0] = on ? __byte_perm(h, l, 0x5410) : 0u;
    ax[1] = on ? __byte_perm(h, l, 0x7632) : 0u;
    ax[2] = 0u; ax[3] = 0u;
    asm volatile("" : "+r"(ax[0]), "+r"(ax[1]), "+r"(ax[2]), "+r"(ax[3]), "+f"(rsA), "+f"(rsB));
    sched_fence(c);
}

__global__ void __launch_bounds__(384, 1)
fused_layers_kernel(const __grid_constant__ Params prm, const __grid_constant__ CUtensorMap tmQM, const __grid_constant__ CUtensorMap tmQR,
                    const __grid_constant__ CUtensorMap tmWO, const __grid_constant__ CUtensorMap tmW1a, const __grid_constant__ CUtensorMap tmW1b,
                    const __grid_constant__ CUtensorMap tmW2, const __grid_constant__ CUtensorMap tmW2a, const __grid_constant__ CUtensorMap tmOut, const __grid_constant__ CUtensorMap tmX) {
    extern __shared__ __align__(1024) uint8_t smem_raw[];
    const uint32_t sb = smem_u32(smem_raw);
    const int warp = __shfl_sync(0xffffffffu, threadIdx.x >> 5, 0);
    const int lane = threadIdx.x & 31;
    asm volatile("griddepcontrol.launch_dependents;");
    const int cs = 1 << prm.lcs;
    const int cl = prm.role[blockIdx.x >> prm.lcs], p = blockIdx.x & (cs - 1);
    const int r = cl & 7, blk = (cl >> 3) + p;
    const uint16_t mask = (1 << cs) - 1;
    const int role = blk * 8 + r;
    TL(0); TLINIT

    if (warp >= 8 && elect_one()) {
        if (warp == 8) { prefetch_map(&tmQM); prefetch_map(&tmQR); prefetch_map(&tmX); }
        if (warp == 9) {
#pragma unroll
            for (int i = 0; i < NSLOT; i++) { mbar_init(sb + BAR_FULL + i * 8, 1); mbar_init(sb + BAR_EMPTY + i * 8, 8 * cs); }
            mbar_init(sb + BAR_STAGE, 8 * cs);
            mbar_init(sb + BAR_X, 1); mbar_init(sb + BAR_X + 8, 1);
            mbar_init(sb + BAR_CS, 3); mbar_init(sb + BAR_CS + 8, 3);
#pragma unroll
            for (int i = 0; i < NORD; i++) mbar_init(sb + BAR_ORD + i * 8, i < 5 ? cs : 4 * cs);
            asm volatile("fence.mbarrier_init.release.cluster;" ::: "memory");
        }
    }
    __syncwarp();
    asm volatile("barrier.cluster.arrive.relaxed.aligned;" ::: "memory");
    uint32_t etag0;
    asm volatile("{.reg .pred p; setp.ne.s32 p, %2, 8; mov.b32 %0, 0; @p ld.relaxed.gpu.global.u32 %0, [%1];}"
                 : "=r"(etag0) : "l"(prm.scr + (uint32_t)(G_EPOCH + role * 128 + lane * 4)), "r"(warp) : "memory");
    auto load_x = [&](int i) {
        mbar_expect(sb + BAR_X + i * 8, 20480);
        tma2d(sb + STAGE_OFF + i * 20480, &tmX, 80 * (r ^ i), 64 * blk, sb + BAR_X + i * 8);
        tma2d(sb + STAGE_OFF + i * 20480 + 10240, &tmX, 640 + 80 * (r ^ i), 64 * blk, sb + BAR_X + i * 8);
    };
    TL(10);
    asm volatile("barrier.cluster.wait.aligned;" ::: "memory");
    if (warp == 8) {
        TL(1);
        if (elect_one()) {
#pragma unroll 1
            for (int i = 0; i < 2; i++) {
                const uint32_t base = sb + i * slot_off(1), bar = sb + BAR_FULL + i * 8;
                const int row = 80 * (r ^ i);
                mbar_expect(bar, 38400);
#pragma unroll 1
                for (int n = p; n < 4; n += cs) {
                    if (n < 3) tma2d_mc(base + n * 10240, &tmQM, main_col(r) + 640 * n, row, bar, mask);
                    else tma3d_mc(base + 30720, &tmQR, rem_col(r), row, 0, bar, mask);
                }
                if (i == 0) { load_x(0); load_x(1); }
            }
        }
        __syncwarp();
        TL(2);
    }

    if (warp >= 8) {
        int budget = SPIN_BUDGET;
        asm volatile("setmaxnreg.dec.sync.aligned.u32 %0;" :: "n"(REG_HELP));
        if (warp == 8) {
            TL(5);
            if (elect_one()) {
                int slot = 2, use = 0;
#pragma unroll 1
                for (int i = 2; i < NITEMS; i++) {
                    const int k = i >= NITEMS_L ? i - NITEMS_L : i;
                    const uint32_t base = sb + slot_off(slot), bar = sb + BAR_FULL + slot * 8;
                    if (use > 0) mbar_wait(sb + BAR_EMPTY + slot * 8, (use - 1) & 1, budget);
                    if (i == 3) mbar_wait(sb + BAR_STAGE, 0, budget);
                    if (i < NSLOT) mbar_wait(sb + BAR_FULL + (i - 2) * 8, 0, budget);
                    const int n0 = (p + i) & (cs - 1);
                    if (k < 8) {
                        const int np = k < 5 ? 3 : 2, row = 80 * slice_at(k, r), col = main_col(r) + 640 * (3 - np);
                        mbar_expect(bar, np * 10240 + 7680);
#pragma unroll 1
                        for (int n = n0; n <= np; n += cs) {
                            if (n < np) tma2d_mc(base + n * 10240, &tmQM, col + 640 * n, row, bar, mask);
                            else tma3d_mc(base + n * 10240, &tmQR, rem_col(r), row, 0, bar, mask);
                        }
                    } else if (k == 8) {
                        mbar_expect(bar, 30720);
#pragma unroll 1
                        for (int n = n0; n < 3; n += cs) tma2d_mc(base + n * 10240, &tmQM, main_col(r), 80 * slice_at(5 + n, r), bar, mask);
                    } else if (k < IT_W1) {
                        mbar_expect(bar, 30720);
#pragma unroll 1
                        for (int n = n0; n < 6; n += cs) {
                            const int sl = n >= 3, a = n - 3 * sl;
                            tma2d_mc(base + n * 5120, &tmWO, a < 2 ? main_col(r) + 32 * a : rem_col(r), 80 * slice_at(2 * (k - IT_WO) + sl, r), bar, mask);
                        }
                    } else if (k < IT_W2) {
                        const bool full = k < IT_W1 + 6, pb = full ? n0 == 0 : k == IT_W1 + 7;
                        mbar_expect(bar, full ? 35840 : pb ? 40960 : 30720);
                        const int row = 80 * slice_at(full ? k - IT_W1 : 6 + n0, r);
                        if (n0 < 2) {
                            if (pb) tma3d_mc(base + n0 * 20480, &tmW1b, 0, row, 7 * r, bar, mask);
                            else tma3d_mc(base + n0 * (full ? 20480 : 15360), &tmW1a, 0, row, 7 * r + 4, bar, mask);
                        }
                    } else if (k < IT_W2 + 8) {
                        const int st = k - IT_W2, a0 = st < 6 ? 0 : 2;
                        const bool pb = hpartB(st);
                        const int atom = pb ? 8192 : 6144;
                        mbar_expect(bar, (5 - a0) * atom);
                        const int row = 224 * hsrc_at(st, r) + (pb ? 0 : 128);
#pragma unroll 1
                        for (int a = a0 + n0; a < 5; a += cs)
                            tma2d_mc(base + (a - a0) * atom, pb ? &tmW2 : &tmW2a, a < 4 ? main_col(r ^ (a >> 1)) + 32 * (a & 1) : 160 * (r >> 1) + 64, row, bar, mask);
                    } else {
                        mbar_expect(bar, 32768);
#pragma unroll 1
                        for (int n = n0; n < 4; n += cs) tma2d_mc(base + n * 8192, &tmW2, main_col(r) + 32 * (n & 1), 224 * hsrc_at(6 + (n >> 1), r), bar, mask);
                    }
                    if (i == 2) TL(3);
                    if (i == 3) { prefetch_map(&tmWO); prefetch_map(&tmW1a); prefetch_map(&tmW1b); prefetch_map(&tmW2); prefetch_map(&tmW2a); }
                    if (i == NITEMS - 1) prefetch_map(&tmOut);
                    if (++slot == NSLOT) { slot = 0; use++; }
                }
            }
            __syncwarp();
            TLDUMP(16);
        } else {
#pragma unroll 1
            for (int i = threadIdx.x - 288; i < XTRA_BYTES / 16; i += 96)
                asm volatile("st.shared.v4.u32 [%0], {%1,%1,%1,%1};" :: "r"(sb + OFF_XQM + i * 16), "r"(0) : "memory");
            asm volatile("bar.sync 5, 96;" ::: "memory");
            const uint32_t etag = (launder(etag0) & 1u) ^ 1u;
            if (lane < 10) {
                char* cs = prm.scr + (uint32_t)(G_CS + (r * 6 + warp - 9) * 5120 + blk * 320 + lane * 32);
#pragma unroll
                for (int i = 0; i < 4; i++) stv(cs + (i >> 1) * 3 * 5120 + (i & 1) * 16, etag ^ 1u, 0u, 0u, 0u);
            }
            mbar_wait(sb + BAR_X, 0, budget);
            TLH(11);
#pragma unroll 1
            for (int mat = 0; mat < 2; mat++) {
                const int lane = launder(threadIdx.x & 31), j = launder(warp) - 9;
                const int rp = lane < 30 ? (lane * 13) >> 7 : 2, ch = lane < 30 ? lane - 10 * rp : 0;
                const int col = mat ? 224 * r + 80 * j + 8 * ch : 640 * j + 80 * r + 8 * ch;
                const bool valid = !mat || (10 * j + ch < 28 && col < DFF);
                float a[8] = {0.f, 0.f, 0.f, 0.f, 0.f, 0.f, 0.f, 0.f};
                auto sum_rows = [&](const __nv_bfloat16* w0, auto pitch_c) {
                    constexpr int PITCH = decltype(pitch_c)::value;
                    const char* src = reinterpret_cast<const char*>(w0 + (40 * blk + rp) * PITCH + (valid ? col : 0));
#pragma unroll 1
                    for (int h = 0; h < 2; h++) {
                        uint32_t w[7][4];
                        const bool last = h == 0 || rp == 0;
#pragma unroll
                        for (int i = 0; i < 6; i++) ldv(w[i], src + i * 6 * PITCH);
                        ldv(w[6], src + (last ? 36 * PITCH : 0));
#pragma unroll
                        for (int i = 0; i < 7; i++)
#pragma unroll
                            for (int e = 0; e < 4; e++) {
                                const uint32_t v = (i < 6 || last) ? w[i][e] : 0u;
                                a[2 * e] += bf_lo(v); a[2 * e + 1] += bf_hi(v);
                            }
                        src += 42 * PITCH;
                    }
                };
                auto prefetch_w1 = [&]() {
                    const int c1 = 224 * r + 80 * j + 8 * ch;
                    if (10 * j + ch < 28 && c1 < DFF && !(ch & 1)) {
                        const __nv_bfloat16* pf = prm.w1 + (40 * blk + rp) * DFF + c1;
#pragma unroll
                        for (int i = 0; i < 13; i++) asm volatile("prefetch.global.L2 [%0];" :: "l"(pf + 3 * i * DFF));
                        if (rp == 0) asm volatile("prefetch.global.L2 [%0];" :: "l"(pf + 39 * DFF));
                    }
                    __syncwarp();
                };
                if (mat == 0) {
                    sum_rows(prm.wqkv, IntC<DQKV>());
                } else {
                    sum_rows(prm.w1, IntC<DFF>());
                }
                char* cs = prm.scr + (uint32_t)(G_CS + ((r * 2 + mat) * 3 + j) * 5120);
#pragma unroll
                for (int i = 0; i < 8; i++) {
                    a[i] += __shfl_down_sync(0xffffffffu, a[i], 10) + __shfl_down_sync(0xffffffffu, a[i], 20);
                    a[i] = valid ? a[i] : 0.f;
                }
                if (lane < 10) {
                    char* dst = cs + blk * 320 + lane * 32;
                    stv(dst, tagged(__float_as_uint(a[0]), etag), __float_as_uint(a[1]), __float_as_uint(a[2]), __float_as_uint(a[3]));
                    stv(dst + 16, tagged(__float_as_uint(a[4]), etag), __float_as_uint(a[5]), __float_as_uint(a[6]), __float_as_uint(a[7]));
                }
                if (mat == 0) {
                    TLH(12);
                    prefetch_w1();
                }
                cs += (lane < 20 ? lane : 0) * 16;
                a[0] = 0.f; a[1] = 0.f; a[2] = 0.f; a[3] = 0.f;
#pragma unroll 1
                for (int b0 = 0; b0 < 2;) {
                    uint32_t v[8][4];
#pragma unroll
                    for (int i = 0; i < 8; i++) ldv(v[i], cs + i * 320);
                    if (bad_vecs(v, etag) && --budget >= 0) continue;
#pragma unroll
                    for (int i = 0; i < 8; i++)
#pragma unroll
                        for (int e = 0; e < 4; e++) a[e] -= __uint_as_float(v[i][e]);
                    b0++;
                    cs += 8 * 320;
                }
                if (mat == 0) TLH(14);
                const uint32_t h0 = pack2(a[0], a[1]), h1 = pack2(a[2], a[3]);
                const uint32_t l0 = pack2(a[0] - bf_lo(h0), a[1] - bf_hi(h0)), l1 = pack2(a[2] - bf_lo(h1), a[3] - bf_hi(h1));
                const int cc = 4 * launder(lane), cm = cc - 16 * (r & 1), cw = 80 * j + cc;
                const bool mainp = cm >= 0 && cm < 64;
                const uint32_t sh = mat ? 6 : mainp ? 7 : 5;
                const uint32_t ad = sb + (mat ? OFF_XW1 + (cw >> 5) * 512 + (cw & 31) * 2 : mainp ? OFF_XQM + j * 1024 + cm * 2 : OFF_XQR + j * 256 + (cc & 15) * 2);
                if (cc < 80 && (!mat || cw < 224)) {
#pragma unroll
                    for (int row = 0; row < 4; row++) {
                        const uint32_t o = row << sh;
                        asm volatile("st.shared.v2.u32 [%0], {%1,%2};" :: "r"((ad + o) ^ ((o >> 7) << 4)), "r"(row < 2 ? h0 : l0), "r"(row < 2 ? h1 : l1) : "memory");
                    }
                }
                asm volatile("fence.proxy.async.shared::cta;" ::: "memory");
                __syncwarp();
                if (lane == 0) mbar_arrive(sb + BAR_CS + mat * 8);
                TLH(6 + mat);
            }
        }
    } else {
        TL(11);
        TL(12);
        __syncwarp();
        asm volatile("setmaxnreg.inc.sync.aligned.u32 %0;" :: "n"(REG_CONS));
        TL(14);
        Ctx c;
        c.sb = sb; c.sb16 = (sb & 0x3FFFF) >> 4; c.r = r; c.warp = warp; c.layer = 0; c.budget = SPIN_BUDGET; c.eall = __ballot_sync(0xffffffffu, !(launder(etag0) & 1u));
        c.mb = reinterpret_cast<char*>(__shfl_sync(0xffffffffu, reinterpret_cast<size_t>(prm.scr + (uint32_t)(blk * BBOX + r * RBOX + warp * WBOX + lane * 16)), lane));
        asm volatile("mapa.shared::cluster.u32 %0, %1, %2;" : "=r"(c.rel_addr) : "r"(sb + BAR_EMPTY), "r"(lane & (cs - 1)));
        c.rel_addr = __shfl_sync(0xffffffffu, lane < cs ? c.rel_addr : 0, lane);
        uint32_t X[5][4];
        float xv[40];
        unstage(c, X, r & 1, 0);
        TL(15);
        wait_full(c, 0);
        TL(13);
        unpack_x(xv, X);
        park_x(c, X);
        TL(1);

        const int r_ = r, blk_ = blk, warp_ = warp;
#define PHASE_IDS const int r = launder(r_), blk = launder(blk_), warp = launder(warp_), wg = warp >> 2, w = warp & 3; \
                  c.r = r; c.warp = warp; c.sb = launder(sb); c.sb16 = (c.sb & 0x3FFFF) >> 4; const uint32_t etag = launder(c.eall) & 1u; (void)etag; (void)blk; (void)wg; (void)w;
#pragma unroll 1
        for (int layer = 0;; layer++) {
            c.layer = layer;
            float rsA, rsB;
            uint32_t O[5][4];
            {
                PHASE_IDS
                GQKV q;
                Gather<3, V_X, 1u> ga;
                uint32_t ax[4];
                auto hook = [&](int st) {
                    if (st == -1) {
                        if (layer == 0) {
                            unstage(c, ga.buf[0], (r & 1) ^ 1, 1);
#pragma unroll
                            for (int u = 0; u < 5; u++) ga.buf[0][u][0] |= 1u;
                            if (c.rel_addr != 0) mbar_arrive_cluster(c.rel_addr + (BAR_STAGE - BAR_EMPTY));
                        } else {
                            ga.fetch(c, 1);
                        }
                    }
                    if (st >= 1 && layer == 0) {
                        if (st == CLR_HALO && w == 3) {
#pragma unroll
                            for (int u = 0; u < 6; u++) stv(c.mb + voff(V_HALO + u), etag ^ 1u, 0u, 0u, 0u);
                        }
#pragma unroll
                        for (int u = 0; u < 5; u++)
                            if (st == ((CLR_O >> (4 * u)) & 15)) stv(c.mb + voff(V_O + u), 0u, 0u, 0u, 0u);
                    }
                };
                publish(c, X, V_X, 1u);
                ln_head<0, 4, 1u>(q, ga, c, X, xv, rsA, rsB, ax, hook, (TLSEL == 1 + layer * 4) ? 50 : 0);
                float qm[32], kv[64];
                wg_wait<0>();
                reg_fence(q.m);
                rename<32, 0>(qm, q.m);
                rename<64, 32>(kv, q.m);
#pragma unroll
                for (int st = 5; st < 8; st++) {
                    if (st == 7) order_wait<0>(c);
                    wg_fence();
#pragma unroll
                    for (int u = 0; u < 5; u++) {
                        wgmma_n128_acc(kv, ga.at(st)[u], mkdesc(c.sb16, slot_off(st) + kstep(st & 1, u) * 2048, 10240, 1024, 1));
                        wgmma_n48_acc(q.r, ga.at(st)[u], mkdesc(c.sb16, slot_off(st) + 20480 + kstep(st & 1, u) * 512, 2560, 256, 3));
                    }
                    if (st == 7) {
                        wgmma_n128_acc(kv, ax, mkdesc(c.sb16, OFF_XQM + 1024, 1024, 0, 1));
                        wgmma_n48_acc(q.r, ax, mkdesc(c.sb16, OFF_XQR, 256, 0, 3));
                    }
                    wg_commit();
                    if (st == 7) order_post<0>(c);
                    if (st > 5) wg_wait<1>();
                    release(c, st - 1);
                    wait_full(c, st + 1);
                    if (st == 5) {
                        ga.check(c, 6);
                        ga.fetch(c, 7);
                        sched_fence(c);
                    }
                    if (st == 6) {
                        if (layer == 0) mbar_wait(c.sb + BAR_CS, 0, c.budget);
                        ga.check(c, 7);
                    }
                }
                float rk1[2], rk2[2];
                {
                    const int t8 = (c.lane16() >> 1) & 24;
#pragma unroll
                    for (int e = 0; e < 2; e++) {
                        rk2[e] = __shfl_sync(0xffffffffu, rsB, t8 + 4 * e);
                        rk1[e] = __shfl_sync(0xffffffffu, rsA, t8 + 4 * e);
                    }
                }
                auto q_steps = [&](int n0, int n1) {
                    wg_fence();
#pragma unroll
                    for (int n = n0; n < n1; n++) {
                        if (n < 15) wgmma_n64_acc(qm, ga.at(5 + n / 5)[n % 5], mkdesc(c.sb16, slot_off(8) + (n / 5 * 5 + kstep((5 + n / 5) & 1, n % 5)) * 2048, 1024, 1024, 1));
                        else wgmma_n64_acc(qm, ax, mkdesc(c.sb16, OFF_XQM, 1024, 0, 1));
                    }
                    wg_commit();
                };
                q_steps(0, QN0);
                wg_wait<1>();
                reg_fence(kv);
                reg_fence(q.r);
                release(c, 7);
                TL(2 + layer * 16);
                uint32_t T[3][10][2];
                auto pack_tiles = [&](int pc, int h, bool odd) {
#pragma unroll
                    for (int j = 0; j < 10; j++) {
                        const bool isrem = odd ? j < 2 : j >= 8;
                        const int e = isrem ? pc * 8 + 4 * (j & 1) + 2 * h : 4 * ((odd ? j + 6 : j) & 7) + 2 * h;
                        if (isrem) T[pc][j][h] = pack2(q.r[e], q.r[e + 1]);
                        else T[pc][j][h] = pc == 0 ? pack2(qm[e], qm[e + 1]) : pack2(kv[(pc - 1) * 32 + e], kv[(pc - 1) * 32 + e + 1]);
                    }
                };
                if (r & 1) { pack_tiles(1, 1, true); pack_tiles(2, 1, true); }
                else { pack_tiles(1, 1, false); pack_tiles(2, 1, false); }
                auto hreg = [&](int n) -> uint32_t& { return n < 8 ? T[1][n + (n + 2) / 4][1] : n < 10 ? T[1][5 * n - 38][1] : T[2][n - 10][1]; };
                if (w == 3) {
                    char* hg = c.mb + layer * (2 * PLANE);
#pragma unroll
                    for (int u = 0; u < 5; u++) {
                        hreg(4 * u) = tagged(hreg(4 * u), etag);
                        stv(hg + voff(V_HALO + u), hreg(4 * u), hreg(4 * u + 1), hreg(4 * u + 2), hreg(4 * u + 3));
                    }
                    stv(hg + voff(V_HALO + 5), tagged(__float_as_uint(rk2[0]), etag), __float_as_uint(rk2[1]), 0u, 0u);
                }
                if (r & 1) { pack_tiles(1, 0, true); pack_tiles(2, 0, true); }
                else { pack_tiles(1, 0, false); pack_tiles(2, 0, false); }
                unpark_x(c, X);
                if (QPOS == 1) { gate_wait<5, 0>(c); q_steps(QN0, 16); }
                if (w < 3) {
                    const uint32_t hs = c.park();
#pragma unroll
                    for (int u = 0; u < 5; u++) stsm4(hs + u * 512, hreg(4 * u), hreg(4 * u + 1), hreg(4 * u + 2), hreg(4 * u + 3));
                    if (c.lane16() < 64) asm volatile("st.shared.v2.f32 [%0], {%1,%2};" :: "r"(c.sb + OFF_RK + warp * 32 + (c.lane16() >> 1)), "f"(rk2[0]), "f"(rk2[1]) : "memory");
                }
                asm volatile("bar.sync %0, 128;" :: "r"(1 + wg) : "memory");
                uint32_t H[6][4];
                auto hfetch = [&]() { ld_vecs(H, c.mb + (3 * WBOX - BBOX) + layer * (2 * PLANE), V_HALO); };
                if (w > 0) {
                    const uint32_t hs = c.park() - 2560;
                    ldsm4(H[0], hs); ldsm4(H[1], hs + 512);
                    asm volatile("ldmatrix.sync.aligned.m8n8.x2.shared.b16 {%0,%1}, [%2];" : "=r"(H[2][0]), "=r"(H[2][1]) : "r"(hs + 1024) : "memory");
                    asm volatile("ldmatrix.sync.aligned.m8n8.x2.trans.shared.b16 {%0,%1}, [%2];" : "=r"(H[2][2]), "=r"(H[2][3]) : "r"(hs + 1280) : "memory");
                    ldsm4t(H[3], hs + 1536); ldsm4t(H[4], hs + 2048);
                    asm volatile("ld.shared.v2.u32 {%0,%1}, [%2];" : "=r"(H[5][0]), "=r"(H[5][1]) : "r"(c.sb + OFF_RK + warp * 32 - 32 + ((c.lane16() >> 1) & 24)) : "memory");
                    H[5][2] = 0u; H[5][3] = 0u;
                } else if (blk > 0) {
                    hfetch();
                } else {
#pragma unroll
                    for (int u = 0; u < 6; u++) { H[u][0] = 0u; H[u][1] = 0u; H[u][2] = 0u; H[u][3] = 0u; }
                }
                auto hK = [&](int j) { return j == 2 ? H[2][0] : j == 7 ? H[2][1] : H[(j - (j + 2) / 5) >> 2][(j - (j + 2) / 5) & 3]; };
                auto hV = [&](int j) { return H[(j + 10) >> 2][(j + 10) & 3]; };
                uint32_t Vt1[10], Vt2[10];
#pragma unroll
                for (int j = 0; j < 10; j++) { Vt1[j] = movm(T[2][j][0]); Vt2[j] = movm(T[2][j][1]); }
                if (QPOS == 2) { sched_fence(c); gate_wait<5, 0>(c); q_steps(QN0, 16); }
                wg_wait<0>();
                reg_fence(qm);
                release(c, 8);
                if (r & 1) { pack_tiles(0, 0, true); pack_tiles(0, 1, true); }
                else { pack_tiles(0, 0, false); pack_tiles(0, 1, false); }
                TL(3 + layer * 16);
                const int g = c.lane() >> 2, t = c.lane() & 3;
                const bool sel0 = 2 * t > g, sel1 = 2 * t + 1 > g;
                const float cs = 0.22360679774997896f * 1.4426950408889634f;
                const float kB0 = sel0 ? rk1[0] : rk2[0], kB1 = sel1 ? rk1[1] : rk2[1];
                const float fB0 = rsB * cs * kB0, fB1 = rsB * cs * kB1;
                float lA0[4], lA1[4], lB0[4], lB1[4];
                uint32_t qs[4][2];
#pragma unroll
                for (int h = 0; h < 4; h++) {
                    const int f0 = 5 * (h >> 1) + 3 * (h & 1), f1 = f0 + 1, s = 5 * (h >> 1) + 2;
                    const bool keep = (h & 1) ? (t >= 2) : (t < 2);
                    qs[h][0] = keep ? T[0][s][0] : 0u; qs[h][1] = keep ? T[0][s][1] : 0u;
                    float s1[4], s2[4];
                    mma_k8_init(s1, qs[h][0], qs[h][1], T[1][s][0]);
                    mma_k8_init(s2, qs[h][0], qs[h][1], T[1][s][1]);
                    mma_k16_acc(s1, T[0][f0][0], T[0][f0][1], T[0][f1][0], T[0][f1][1], T[1][f0][0], T[1][f1][0]);
                    mma_k16_acc(s2, T[0][f0][0], T[0][f0][1], T[0][f1][0], T[0][f1][1], T[1][f0][1], T[1][f1][1]);
                    lA0[h] = s1[0]; lA1[h] = s1[1];
                    lB0[h] = (sel0 ? s1[2] : s2[2]) * fB0;
                    lB1[h] = (sel1 ? s1[3] : s2[3]) * fB1;
                }
                wait_full(c, IT_WO);
                if (w == 0 && blk > 0) {
                    check_vecs(c, H, etag, hfetch);
#pragma unroll
                    for (int n = 10; n < 20; n++) H[n >> 2][n & 3] = movm(H[n >> 2][n & 3]);
                }
                const bool first = (blk == 0) && (w == 0);
                const float kA0 = sel0 ? __uint_as_float(H[5][0]) : rk1[0], kA1 = sel1 ? __uint_as_float(H[5][1]) : rk1[1];
                const float fA0 = rsA * cs * kA0, fA1 = rsA * cs * kA1;
                const float bA0 = (first && sel0) ? -INFINITY : 0.f, bA1 = (first && sel1) ? -INFINITY : 0.f;
                const uint32_t M = (sel0 ? 0x0000ffffu : 0u) | (sel1 ? 0xffff0000u : 0u);
#pragma unroll
                for (int h = 0; h < 4; h++) {
                    const int f0 = 5 * (h >> 1) + 3 * (h & 1), f1 = f0 + 1, s = 5 * (h >> 1) + 2;
                    float s0[4];
                    mma_k8_init(s0, qs[h][0], qs[h][1], hK(s));
                    mma_k16_acc(s0, T[0][f0][0], T[0][f0][1], T[0][f1][0], T[0][f1][1], hK(f0), hK(f1));
                    lA0[h] = fmaf(sel0 ? s0[0] : lA0[h], fA0, bA0);
                    lA1[h] = fmaf(sel1 ? s0[1] : lA1[h], fA1, bA1);
                }
                if (((ORDER >> 5) & 1) && QPOST == 0) {
                    reg_fence(lA0); reg_fence(lA1);
                    sched_fence(c);
                    gate_post<5, 0>(c);
                }
                uint32_t pA[4], pB[4];
#pragma unroll
                for (int h = 0; h < 4; h++) {
                    float mA = fmaxf(lA0[h], lA1[h]), mB = fmaxf(lB0[h], lB1[h]);
                    mA = fmaxf(mA, __shfl_xor_sync(0xffffffffu, mA, 1));
                    mB = fmaxf(mB, __shfl_xor_sync(0xffffffffu, mB, 1));
                    mA = fmaxf(mA, __shfl_xor_sync(0xffffffffu, mA, 2));
                    mB = fmaxf(mB, __shfl_xor_sync(0xffffffffu, mB, 2));
                    const float eA0 = ex2(lA0[h] - mA), eA1 = ex2(lA1[h] - mA), eB0 = ex2(lB0[h] - mB), eB1 = ex2(lB1[h] - mB);
                    float sA = eA0 + eA1, sB = eB0 + eB1;
                    sA += __shfl_xor_sync(0xffffffffu, sA, 1);
                    sB += __shfl_xor_sync(0xffffffffu, sB, 1);
                    sA += __shfl_xor_sync(0xffffffffu, sA, 2);
                    sB += __shfl_xor_sync(0xffffffffu, sB, 2);
                    const float iA = rcp(sA), iB = rcp(sB);
                    pA[h] = pack2(eA0 * kA0 * iA, eA1 * kA1 * iA);
                    pB[h] = pack2(eB0 * kB0 * iB, eB1 * kB1 * iB);
                }
#pragma unroll
                for (int h = 0; h < 4; h++) {
                    const int f0 = 5 * (h >> 1) + 3 * (h & 1), s = 5 * (h >> 1) + 2;
                    const uint32_t ap = pA[h] & M, a0 = pA[h] & ~M, a1 = pB[h] & M, a3 = pB[h] & ~M;
#pragma unroll
                    for (int i = 0; i < 3; i++) {
                        const int j = i < 2 ? f0 + i : s;
                        float o[4];
                        mma_k8_init(o, ap, 0u, hV(j));
                        mma_k16_acc(o, a0, a1, 0u, a3, Vt1[j], Vt2[j]);
                        const uint32_t o0 = pack2(o[0], o[1]), o1 = pack2(o[2], o[3]);
                        uint32_t& d0 = O[j >> 1][2 * (j & 1)];
                        uint32_t& d1 = O[j >> 1][2 * (j & 1) + 1];
                        if (i < 2 || (h & 1) == 0) { d0 = o0; d1 = o1; }
                        else { d0 = t >= 2 ? o0 : d0; d1 = t >= 2 ? o1 : d1; }
                    }
                }
                if ((ORDER >> 5) & 3) {
                    sched_fence(c);
                    if (QPOST == 1) gate_post<5, 0>(c);
                    gate_post<6, 1>(c);
                }
                publish(c, O, V_O, 1u);
            }
            TL(4 + layer * 16);
            {
                PHASE_IDS
                Gather<7, V_O, 1u> ga;
                sched_fence(c);
                unpack_x(xv, X);
#pragma unroll
                for (int st = 0; st < 8; st++) {
                    if (st == OW1) order_wait<1>(c);
                    if (st == G6AT) gate_wait<6, 1>(c);
                    wg_fence();
#pragma unroll
                    for (int u = 0; u < 5; u++)
                        wgmma_n80_acc(xv, st == 0 ? O[u] : ga.at(st > 0 ? st : 1)[u], mkdesc(c.sb16, slot_off(IT_WO + st / 2) + (st & 1) * 15360 + u * 1024, 5120, 512, 2));
                    wg_commit();
                    if (st == 7) order_post<1>(c);
                    if (st > 0 && (st & 1) == 0) { wg_wait<1>(); release(c, IT_WO + st / 2 - 1); }
                    auto CHK = [](int i) { return i < 0 ? 0 : (int)((WO_CHK >> (4 * i)) & 15); };
                    auto FET = [](int i) { return i < 0 ? 0 : (int)((WO_FET >> (4 * i)) & 15); };
                    if (st & 1) wait_full(c, IT_WO + st / 2 + 1); else if (CHK(st) > CHK(st - 1)) sched_fence(c);
                    if (st == 0) {
                        order_wait<2>(c);
#pragma unroll
                        for (int i = 1; i <= WO_F0; i++) ga.fetch(c, i);
                    }
#pragma unroll
                    for (int i = CHK(st - 1) + 1; i <= CHK(st); i++) ga.check(c, i);
#pragma unroll
                    for (int i = (st == 0 ? WO_F0 : FET(st - 1)) + 1; i <= FET(st); i++) ga.fetch(c, i);
                    if (st == GP) order_post<2>(c);
                    if (FET(st) > FET(st - 1)) sched_fence(c);
                    if (TLSEL == 2 + layer * 4) TL(50 + st);
                }
                wg_wait<0>();
                reg_fence(xv);
                release(c, IT_W1 - 1);
                TL(5 + layer * 16);
                pack_x(X, xv);
                if (DBG_STAGE == 1 + 2 * layer) store_out(c, X, &tmOut, blk);
                park_x(c, X);
                publish(c, X, V_X, 0u);
            }
            TL(6 + layer * 16);
            {
                PHASE_IDS
                const uint32_t ltag = layer ^ 1u;
                uint32_t Ha[6][4], Hb[8][4];
                {
                    GW1 f;
                    Gather<3, V_X, 0u> ga;
                    uint32_t ax[4];
                    ln_head<IT_W1, 5, 0u>(f, ga, c, X, xv, rsA, rsB, ax, [&](int st) {
                        if (st == -1) ga.fetch(c, 1);
                        if (st == 2 && layer == 0) {
                            stv(c.mb + voff(V_HB + 7), 0u, 0u, 0u, 0u);
                            stv(c.mb + voff(V_HA + 5), 0u, 0u, 0u, 0u);
                        }
                        if (st == 3 && layer == 0 && w == 3) {
#pragma unroll
                            for (int u = 0; u < 6; u++) stv(c.mb + voff(V_HALO + 10 + u), etag ^ 1u, 0u, 0u, 0u);
                        }
                    }, (TLSEL == 3 + layer * 4) ? 50 : 0);
                    float fa[48], fb[64];
                    if (layer == 0) mbar_wait(c.sb + BAR_CS + 8, 0, c.budget);
                    wg_wait<0>();
                    reg_fence(f.m);
                    rename<64, 0>(fb, f.m);
                    rename<48, 64>(fa, f.m);
#pragma unroll
                    for (int st = 6; st < 8; st++) {
                        wg_fence();
#pragma unroll
                        for (int u = 0; u < 5; u++)
                            wgmma_n96_acc(fa, ga.at(st)[u], mkdesc(c.sb16, slot_off(IT_W1 + 6) + (st - 6) * 15360 + kstep(st & 1, u) * 1024, 5120, 512, 2));
                        if (st == 6) {
                            release(c, IT_W1 + 5);
                            wait_full(c, IT_W1 + 7);
                            ga.check(c, 7);
                        }
                    }
                    wgmma_n96_acc(fa, ax, mkdesc(c.sb16, OFF_XW1 + 2048, 512, 0, 2));
                    wg_commit();
                    auto b_steps = [&](int n0, int n1) {
                        wg_fence();
#pragma unroll
                        for (int n = n0; n < n1; n++) {
                            if (n < 10) wgmma_n128_acc(fb, ga.at(6 + n / 5)[n % 5], mkdesc(c.sb16, slot_off(IT_W1 + 7) + (n / 5) * 20480 + kstep(n / 5, n % 5) * 1024, 5120, 512, 2));
                            else wgmma_n128_acc(fb, ax, mkdesc(c.sb16, OFF_XW1, 512, 0, 2));
                        }
                        wg_commit();
                    };
                    b_steps(0, 7);
                    wait_full(c, IT_W2);
                    wg_wait<1>();
                    reg_fence(fa);
                    release(c, IT_W1 + 6);
                    TL(7 + layer * 16);
#pragma unroll
                    for (int k = 0; k < 6; k++)
#pragma unroll
                        for (int i = 0; i < 4; i++) Ha[k][i] = pack2_relu(fa[8 * k + 2 * i], fa[8 * k + 2 * i + 1]);
                    publish(c, Ha, V_HA, ltag);
                    sched_fence(c);
                    b_steps(7, 11);
                    wg_wait<0>();
                    reg_fence(fb);
#pragma unroll
                    for (int k = 0; k < 8; k++)
#pragma unroll
                        for (int i = 0; i < 4; i++) Hb[k][i] = pack2_relu(fb[8 * k + 2 * i], fb[8 * k + 2 * i + 1]);
                    sched_fence(c);
                }
                float acc[80];
                uint32_t bufa[3][6][4], bufb[3][8][4];
                auto step_a = [&](int st, const uint32_t (&a)[6][4]) {
                    wg_fence();
#pragma unroll
                    for (int k = 0; k < 6; k++) {
                        const uint64_t d = mkdesc(c.sb16, slot_off(IT_W2 + st) + k * 1024, 6144, 512, 2);
                        if (st == 0 && k == 0) wgmma_n160_init(acc, a[k], d); else wgmma_n160_acc(acc, a[k], d);
                    }
                    wg_commit();
                };
                auto step_b = [&](int st, const uint32_t (&a)[8][4]) {
                    wg_fence();
#pragma unroll
                    for (int k = 0; k < 8; k++) wgmma_n160_acc(acc, a[k], mkdesc(c.sb16, slot_off(IT_W2 + st) + k * 1024, 8192, 512, 2));
                    wg_commit();
                };
                auto hprobe = [&](int vec) { if (layer == 0) probe(c, ((c.lane16() >> 3) & 6) + (r & 1), vec); };
                auto hfetch = [&](int st) {
                    if (st < 5) ld_vecs(bufa[st < 5 ? st - 2 : 0], c.box(hsrc_at(st, r)), V_HA);
                    else ld_vecs(bufb[st < 5 ? 0 : st - 5], c.box(hsrc_at(st, r)), V_HB);
                };
                auto hcheck = [&](int st) {
                    if (st < 5) check_vecs(c, bufa[st < 5 ? st - 2 : 0], ltag, [&]() { hfetch(st); });
                    else check_vecs(c, bufb[st < 5 ? 0 : st - 5], ltag, [&]() { hfetch(st); });
                };
                step_a(0, Ha);
                release(c, IT_W1 + 7);
                wait_full(c, IT_W2 + 1);
                hprobe(V_HA + 5);
                hfetch(2);
#pragma unroll
                for (int k = 0; k < 8; k++) Hb[k][0] = launder(tagged(Hb[k][0], ltag));
                auto send_b = [&](int k0, int k1) {
#pragma unroll
                    for (int k = k0; k < k1; k++) stv(c.mb + voff(V_HB + k), Hb[k][0], Hb[k][1], Hb[k][2], Hb[k][3]);
                };
                send_b(0, HB0);
                sched_fence(c);
#pragma unroll
                for (int st = 1; st < 6; st++) {
                    if (st == 1) step_b(1, Hb); else if (st < 5) step_a(st, bufa[st > 1 && st < 5 ? st - 2 : 0]); else step_b(st, bufb[0]);
                    wg_wait<1>();
                    release(c, IT_W2 + st - 1);
                    wait_full(c, IT_W2 + st + 1);
                    hcheck(st + 1);
                    if (st == 3) hprobe(V_HB + 7);
                    hfetch(st + 2);
                    if (st == 1) send_b(HB0, HB1);
                    if (st == 2) send_b(HB1, 8);
                    sched_fence(c);
                    if (layer == TLL) TL(40 + st);
                }
                order_wait<3>(c);
                wg_wait<0>();
                reg_fence(acc);
                float own[32], par[48];
                rename<48, 32>(par, acc);
                rename<32, 0>(own, acc);
#pragma unroll
                for (int st = 6; st < 8; st++) {
                    if (st == 7) { order_post<3>(c); release(c, IT_W2 + 5); wait_full(c, IT_W2 + 7); hcheck(7); order_wait<4>(c); }
                    wg_fence();
#pragma unroll
                    for (int k = 0; k < 8; k++) wgmma_n96_acc(par, bufb[st - 5][k], mkdesc(c.sb16, slot_off(IT_W2 + st) + k * 1024, 8192, 512, 2));
                    wg_commit();
                }
                order_post<4>(c);
                wait_full(c, IT_W2 + 8);
                auto own_step = [&](int i) {
                    wg_fence();
#pragma unroll
                    for (int k = 0; k < 8; k++) wgmma_n64_acc(own, bufb[1 + i][k], mkdesc(c.sb16, slot_off(IT_W2 + 8) + i * 16384 + k * 1024, 8192, 512, 2));
                    wg_commit();
                };
                own_step(0);
                wg_wait<1>();
                reg_fence(par);
                release(c, IT_W2 + 6);
                release(c, IT_W2 + 7);
                float rem[8];
                uint32_t P[5][4];
                {
                    const bool odd = r & 1;
#pragma unroll
                    for (int u = 0; u < 5; u++)
#pragma unroll
                        for (int i = 0; i < 4; i++) {
                            const int e = 8 * u + 2 * i;
                            if (u < 4) P[u][i] = pack2(par[e], par[e + 1]);
                            else P[u][i] = pack2(odd ? par[e] : par[e + 8], odd ? par[e + 1] : par[e + 9]);
                        }
                    publish(c, P, V_O, 0u);
#pragma unroll
                    for (int i = 0; i < 8; i++) rem[i] = odd ? par[40 + i] : par[32 + i];
                }
                sched_fence(c);
                own_step(1);
                if (layer == TLL) TL(47);
                sched_fence(c);
                auto pfetch = [&]() { ld_vecs(P, c.box(r ^ 1), V_O); };
                pfetch();
                unpark_x(c, X);
                wg_wait<0>();
                reg_fence(own);
                release(c, IT_W2 + 8);
#pragma unroll
                for (int u = 0; u < 5; u++)
#pragma unroll
                    for (int i = 0; i < 4; i++) {
                        const float rs = (i & 1) ? rsB : rsA;
                        const int e = 8 * u + 2 * i;
                        xv[e] = fmaf(rs, u < 4 ? own[e & 31] : rem[e & 7], bf_lo(X[u][i]));
                        xv[e + 1] = fmaf(rs, u < 4 ? own[(e + 1) & 31] : rem[(e + 1) & 7], bf_hi(X[u][i]));
                    }
                reg_fence(xv);
                if (layer == 0) wait_full(c, 0); else sched_fence(c);
                check_vecs(c, P, 0u, pfetch);
                TL(8 + layer * 16);
#pragma unroll
                for (int u = 0; u < 5; u++)
#pragma unroll
                    for (int i = 0; i < 4; i++) {
                        const float rs = (i & 1) ? rsB : rsA;
                        const int e = 8 * u + 2 * i;
                        xv[e] = fmaf(rs, bf_lo(P[u][i]), xv[e]);
                        xv[e + 1] = fmaf(rs, bf_hi(P[u][i]), xv[e + 1]);
                    }
                pack_x(X, xv);
                if (layer == 1) break;
                if (DBG_STAGE == 2) store_out(c, X, &tmOut, blk);
                park_x(c, X);
            }
            TL(9 + layer * 16);
        }
        if (DBG_STAGE == 4) store_out(c, X, &tmOut, blk);
        TL(25);
        TLDUMP(64);
        if (warp == 0) reinterpret_cast<unsigned*>(prm.scr + G_EPOCH + role * 128)[c.lane()] = c.eall;
    }
}

typedef CUresult (*EncodeFn)(CUtensorMap*, CUtensorMapDataType, cuuint32_t, void*, const cuuint64_t*, const cuuint64_t*,
                             const cuuint32_t*, const cuuint32_t*, CUtensorMapInterleave, CUtensorMapSwizzle,
                             CUtensorMapL2promotion, CUtensorMapFloatOOBfill);

void encode(EncodeFn fn, CUtensorMap* tm, const void* ptr, int rank, const cuuint64_t* dims, const cuuint64_t* strides,
            const cuuint32_t* box, CUtensorMapSwizzle sw) {
    const cuuint32_t es[3] = {1, 1, 1};
    fn(tm, CU_TENSOR_MAP_DATA_TYPE_BFLOAT16, rank, const_cast<void*>(ptr), dims, strides, box, es, CU_TENSOR_MAP_INTERLEAVE_NONE, sw,
       CU_TENSOR_MAP_L2_PROMOTION_NONE, CU_TENSOR_MAP_FLOAT_OOB_FILL_NONE);
}

__global__ void occupancy_probe_kernel() {}

struct Plan { int lcs, na, nb; uint8_t a[64], b[64]; };
Plan make_plan(int lcs) {
    Plan pl;
    pl.lcs = 1; pl.na = 64; pl.nb = 0;
    for (int i = 0; i < 64; i++) { pl.a[i] = ((i & 7) << 4) | (i >> 3); pl.b[i] = 0; }
    cudaFuncSetAttribute(occupancy_probe_kernel, cudaFuncAttributeMaxDynamicSharedMemorySize, SMEM_BYTES);
    cudaFuncSetAttribute(occupancy_probe_kernel, cudaFuncAttributeNonPortableClusterSizeAllowed, 1);
    int N[17] = {0};
    for (int cs = 2; cs <= 16; cs++) {
        cudaLaunchConfig_t cfg = {};
        cfg.gridDim = dim3(cs * 8); cfg.blockDim = dim3(384); cfg.dynamicSmemBytes = SMEM_BYTES;
        cudaLaunchAttribute at[1];
        at[0].id = cudaLaunchAttributeClusterDimension;
        at[0].val.clusterDim.x = cs; at[0].val.clusterDim.y = 1; at[0].val.clusterDim.z = 1;
        cfg.attrs = at; cfg.numAttrs = 1;
        if (cudaOccupancyMaxActiveClusters(&N[cs], occupancy_probe_kernel, &cfg) != cudaSuccess) { cudaGetLastError(); return pl; }
    }
    int ge[10] = {0};
    for (int k = 5; k <= 8; k++) ge[k] = N[2 * k];
    ge[9] = N[9] - ge[5];
    ge[4] = N[8] - ge[8];
    ge[3] = N[6] - ge[6] - ge[9];
    ge[2] = N[4] - ge[4] - ge[6] - ge[8];
    ge[1] = ge[2];
    int total = 0;
    for (int k = 1; k <= 9; k++) { if (ge[k] < 0 || ge[k] > 16 || (k > 1 && ge[k] > ge[k - 1])) return pl; total += ge[k]; }
    const int singles = N[2] - total;
    if (singles < 0 || N[2] < 64) return pl;
    const int cs = 1 << lcs, tp = cs / 2, want = 128 / cs, na = N[cs] < want ? N[cs] : want;
    int col[64], cnt[17] = {0}, n = 0;
    if (lcs == 1) for (; n < singles && n < na; n++) col[n] = 16;
    for (int k = tp; k <= 9; k += tp)
        for (int j = ge[k] - 1; j >= 0 && n < na; j--) col[n++] = (cnt[j]++ < 16 / cs) ? j : 16;
    if (n != na) return pl;
    pl.lcs = lcs; pl.na = na; pl.nb = (want - na) * tp;
    auto rank_of = [](int q) { return QPAR ? 2 * (q & 3) + (q >> 2) : q; };
    int pos = 0;
    for (int j = 0; j <= 16; j++)
        for (int i = 0; i < na; i++)
            if (col[i] == (j < 8 ? (int)((COLPERM >> (4 * j)) & 15) : j)) { pl.a[i] = (((pos >> 3) * cs) << 3) | rank_of(pos & 7); pos++; }
    for (int i = 0; i < pl.nb; i++) { const int q = na + i / tp; pl.b[i] = (((q >> 3) * cs + 2 * (i % tp)) << 3) | rank_of(q & 7); }
    return pl;
}

}

extern "C" void kernel_launch(void* const* d_in, const int* in_sizes, int n_in, void* d_out, int out_size) {
    const __nv_bfloat16* x = (const __nv_bfloat16*)d_in[0];
    const __nv_bfloat16* wqkv = (const __nv_bfloat16*)d_in[1];
    const __nv_bfloat16* wo = (const __nv_bfloat16*)d_in[2];
    const __nv_bfloat16* w1 = (const __nv_bfloat16*)d_in[4];
    const __nv_bfloat16* w2 = (const __nv_bfloat16*)d_in[5];

    void* fnp = nullptr;
    cudaDriverEntryPointQueryResult qr;
    cudaGetDriverEntryPoint("cuTensorMapEncodeTiled", &fnp, cudaEnableDefault, &qr);
    EncodeFn fn = (EncodeFn)fnp;
    CUtensorMap tmQM, tmQR, tmWO, tmW1a, tmW1b, tmW2, tmW2a, tmOut, tmX;
    {
        const cuuint64_t dims[3] = {640, 640, 3}, strides[2] = {DQKV * 2, 640 * 2};
        const cuuint64_t dims2[2] = {DQKV, 640};
        const cuuint32_t bm[2] = {64, 80}, br[3] = {16, 80, 3};
        encode(fn, &tmQM, wqkv, 2, dims2, strides, bm, CU_TENSOR_MAP_SWIZZLE_128B);
        encode(fn, &tmQR, wqkv, 3, dims, strides, br, CU_TENSOR_MAP_SWIZZLE_32B);
    }
    {
        const cuuint64_t dims[2] = {640, 640}, strides[1] = {640 * 2};
        const cuuint32_t box[2] = {32, 80};
        encode(fn, &tmWO, wo, 2, dims, strides, box, CU_TENSOR_MAP_SWIZZLE_64B);
    }
    {
        const cuuint64_t dims[3] = {32, 640, 54}, strides[2] = {DFF * 2, 64};
        const cuuint32_t boxa[3] = {32, 80, 3}, boxb[3] = {32, 80, 4};
        encode(fn, &tmW1a, w1, 3, dims, strides, boxa, CU_TENSOR_MAP_SWIZZLE_64B);
        encode(fn, &tmW1b, w1, 3, dims, strides, boxb, CU_TENSOR_MAP_SWIZZLE_64B);
    }
    {
        const cuuint64_t dims[2] = {640, DFF}, strides[1] = {640 * 2};
        const cuuint32_t box[2] = {32, 128}, boxa[2] = {32, 96};
        encode(fn, &tmW2, w2, 2, dims, strides, box, CU_TENSOR_MAP_SWIZZLE_64B);
        encode(fn, &tmW2a, w2, 2, dims, strides, boxa, CU_TENSOR_MAP_SWIZZLE_64B);
    }
    {
        const cuuint64_t dims[2] = {1280, 1024}, strides[1] = {1280 * 2};
        const cuuint32_t box[2] = {80, 16};
        encode(fn, &tmOut, d_out, 2, dims, strides, box, CU_TENSOR_MAP_SWIZZLE_NONE);
        const cuuint32_t boxx[2] = {80, 64};
        encode(fn, &tmX, x, 2, dims, strides, boxx, CU_TENSOR_MAP_SWIZZLE_NONE);
    }
    cudaFuncSetAttribute(fused_layers_kernel, cudaFuncAttributeMaxDynamicSharedMemorySize, SMEM_LAUNCH);
    const Plan pl = make_plan(LCS);
    Params prm;
    void* scr = nullptr;
    cudaGetSymbolAddress(&scr, g_scratch);
    prm.scr = (char*)scr;
    prm.wqkv = wqkv; prm.w1 = w1;
    for (int part = 0; part < (pl.nb ? 2 : 1); part++) {
        prm.lcs = part ? 1 : pl.lcs;
        for (int i = 0; i < 64; i++) prm.role[i] = part ? pl.b[i] : pl.a[i];
        cudaLaunchConfig_t cfg = {};
        cfg.gridDim = dim3((part ? pl.nb : pl.na) << prm.lcs); cfg.blockDim = dim3(384); cfg.dynamicSmemBytes = SMEM_LAUNCH;
        cfg.stream = cudaStreamPerThread;
        cudaLaunchAttribute at[2];
        at[0].id = cudaLaunchAttributeClusterDimension;
        at[0].val.clusterDim.x = 1 << prm.lcs; at[0].val.clusterDim.y = 1; at[0].val.clusterDim.z = 1;
        at[1].id = cudaLaunchAttributeProgrammaticStreamSerialization;
        at[1].val.programmaticStreamSerializationAllowed = 1;
        cfg.attrs = at; cfg.numAttrs = part ? 2 : 1;
        cudaLaunchKernelEx(&cfg, fused_layers_kernel, prm, tmQM, tmQR, tmWO, tmW1a, tmW1b, tmW2, tmW2a, tmOut, tmX);
    }
}
```
